```python
import torch

def _softmax(x, axis=-1):
    return torch.softmax(x, dim=axis)
def _gelu(x):
    return torch.nn.functional.gelu(x, approximate="tanh")
def _silu(x):
    return torch.nn.functional.silu(x)
def _sigmoid(x):
    return torch.sigmoid(x)
def _layernorm(x, axis=-1, eps=1e-5):
    m = x.mean(dim=axis, keepdim=True)
    v = x.var(dim=axis, keepdim=True, unbiased=False)
    return (x - m) / torch.sqrt(v + eps)
def _scatter_add(tgt, idx, src, axis=0):
    return tgt.clone().index_add_(axis, idx, src)
def _segment_sum(src, seg, n):
    out = torch.zeros((n,) + src.shape[1:], dtype=src.dtype)
    return out.index_add_(0, seg, src)
def _pad(x, pw):
    flat = tuple(v for pair in reversed(pw) for v in pair)
    return torch.nn.functional.pad(x, flat)

kernel_name = 'concat_heads__gqa_block_cached__gqa_block_cached__decode'

def setup_inputs():

    _w = (lambda a: (lambda t: t.to(torch.bfloat16) if t.is_floating_point() else t)(torch.as_tensor(a)))
    def _A_setup():
        B, Sq, D = 1, 1, 576
        Hq, Hkv, Sk, Dh = 32, 16, 8192, 128
        assert Hq % Hkv == 0, (Hq, Hkv)
        return {
            "x": _w((lambda *s: torch.randn(*s, dtype=torch.bfloat16) * 0.8)(B, Sq, D)),
            "k_cache": _w((lambda *s: torch.randn(*s, dtype=torch.bfloat16) * 0.8)(B, Hkv, Sk, Dh)),
            "v_cache": _w((lambda *s: torch.randn(*s, dtype=torch.bfloat16) * 0.05)(B, Hkv, Sk, Dh)),
            "wq": _w((lambda *s: torch.randn(*s, dtype=torch.bfloat16) * 0.8)(D, Hq * Dh) * (D ** -0.5)),
            "wo": _w((lambda *s: torch.randn(*s, dtype=torch.bfloat16) * 0.05)(Hq * Dh, D) * ((Hq * Dh) ** -0.5)),
        }
    _A_in = _A_setup()

    def _B_setup():
        B, Sq, D = 1, 1, 576
        Hq, Hkv, Sk, Dh = 32, 16, 8192, 128
        assert Hq % Hkv == 0, (Hq, Hkv)
        return {
            "x": _w((lambda *s: torch.randn(*s, dtype=torch.bfloat16) * 0.8)(B, Sq, D)),
            "k_cache": _w((lambda *s: torch.randn(*s, dtype=torch.bfloat16) * 0.8)(B, Hkv, Sk, Dh)),
            "v_cache": _w((lambda *s: torch.randn(*s, dtype=torch.bfloat16) * 0.05)(B, Hkv, Sk, Dh)),
            "wq": _w((lambda *s: torch.randn(*s, dtype=torch.bfloat16) * 0.8)(D, Hq * Dh) * (D ** -0.5)),
            "wo": _w((lambda *s: torch.randn(*s, dtype=torch.bfloat16) * 0.05)(Hq * Dh, D) * ((Hq * Dh) ** -0.5)),
        }
    _B_in = _B_setup()

    return {
        "A_x": _A_in["x"],
        "A_k_cache": _A_in["k_cache"],
        "A_v_cache": _A_in["v_cache"],
        "A_wq": _A_in["wq"],
        "A_wo": _A_in["wo"],
        "B_x": _B_in["x"],
        "B_k_cache": _B_in["k_cache"],
        "B_v_cache": _B_in["v_cache"],
        "B_wq": _B_in["wq"],
        "B_wo": _B_in["wo"],
    }

def reference(A_x, A_k_cache, A_v_cache, A_wq, A_wo, B_x, B_k_cache, B_v_cache, B_wq, B_wo):
    def _A_ref(x, k_cache, v_cache, wq, wo):
        B, Sq, D = x.shape
        Hq, Dh = 32, 128
        Hkv = k_cache.shape[1]
        rep = Hq // Hkv
        q = (lambda x, *d: x.permute(*d))((x @ wq).reshape(B, Sq, Hq, Dh), 0, 2, 1, 3)
        k = (lambda x, n, axis: torch.repeat_interleave(x, n, dim=axis))(k_cache, rep, axis=1)
        v = (lambda x, n, axis: torch.repeat_interleave(x, n, dim=axis))(v_cache, rep, axis=1)
        scores = torch.einsum("bhqd,bhkd->bhqk", q, k) * (Dh ** -0.5)
        p = _softmax(scores, axis=-1)
        o = torch.einsum("bhqk,bhkd->bhqd", p, v)
        return (lambda x, *d: x.permute(*d))(o, 0, 2, 1, 3).reshape(B, Sq, Hq * Dh) @ wo

    def _B_ref(x, k_cache, v_cache, wq, wo):
        B, Sq, D = x.shape
        Hq, Dh = 32, 128
        Hkv = k_cache.shape[1]
        rep = Hq // Hkv
        q = (lambda x, *d: x.permute(*d))((x @ wq).reshape(B, Sq, Hq, Dh), 0, 2, 1, 3)
        k = (lambda x, n, axis: torch.repeat_interleave(x, n, dim=axis))(k_cache, rep, axis=1)
        v = (lambda x, n, axis: torch.repeat_interleave(x, n, dim=axis))(v_cache, rep, axis=1)
        scores = torch.einsum("bhqd,bhkd->bhqk", q, k) * (Dh ** -0.5)
        p = _softmax(scores, axis=-1)
        o = torch.einsum("bhqk,bhkd->bhqd", p, v)
        return (lambda x, *d: x.permute(*d))(o, 0, 2, 1, 3).reshape(B, Sq, Hq * Dh) @ wo

    a = _A_ref(A_x, A_k_cache, A_v_cache, A_wq, A_wo)
    b = _B_ref(B_x, B_k_cache, B_v_cache, B_wq, B_wo)
    return torch.concatenate([a, b], axis=-1)
```

```cpp
#include <cuda_runtime.h>
#include <cuda_bf16.h>
#include <stdint.h>

namespace {

constexpr int D_MODEL = 576;
constexpr int HKV = 16;
constexpr int SK = 8192;
constexpr int DH = 128;
constexpr int QCOLS = 4096;
constexpr int NSPLIT = 4;
constexpr int NCTA = 2 * HKV * NSPLIT;
constexpr int KEYS_PER_CTA = SK / NSPLIT;
constexpr int TILE_KEYS = 64;
constexpr int TILE_BYTES = TILE_KEYS * DH * 2;
constexpr int NTILES = KEYS_PER_CTA / TILE_KEYS;
#define INFLIGHT 8
#define PACE_DT 650
#define PACE_DTW (PACE_DT * 9 / 8)
#define PACE_T0 2000
#define L2PF 0
constexpr int NS = 12;
constexpr int WO_ROW_BYTES = D_MODEL * 2;
constexpr int WO_CHUNK_BYTES = 16 * WO_ROW_BYTES;
constexpr int SLOT_BYTES = WO_CHUNK_BYTES;
constexpr int WO_SLOT0 = (2 * NTILES) % NS;
constexpr int WO_PHASE = ((2 * NTILES) / NS) & 1;
static_assert(WO_SLOT0 + 4 <= NS, "wo chunks must be contiguous in the ring");
constexpr int WQ_SLOT0 = NS - 4;
constexpr int QROWS_PER_CTA = D_MODEL / NSPLIT;
constexpr int QROWS_PER_WARP = QROWS_PER_CTA / 8;
constexpr int NTHREADS = 320;
constexpr int NRED = 36;
constexpr unsigned SPIN_LIMIT = 1u << 19;

constexpr int SM_RING = 0;
constexpr int SM_WO = SM_RING + WO_SLOT0 * SLOT_BYTES;
constexpr int SM_WQ = SM_RING + WQ_SLOT0 * SLOT_BYTES;
constexpr int SM_RED = SM_RING + NS * SLOT_BYTES;
constexpr int SM_ML = SM_RED + 8 * 256 * 4;
constexpr int SM_Q = SM_ML + 128;
constexpr int SM_O = SM_Q + 512;
constexpr int SM_BAR = SM_O + 128;
constexpr int SM_TL = SM_BAR + (2 * NS + 8) * 8;
constexpr int SM_TOTAL = SM_TL + 128;

constexpr int QBOX_WORDS = NCTA * NSPLIT * 256;
constexpr int OBOX_WORDS = NCTA * NSPLIT * 128;
constexpr int RBOX_WORDS = 2 * NRED * 64 * 16;
__device__ __align__(1024) uint32_t g_mail[QBOX_WORDS + OBOX_WORDS + RBOX_WORDS];

__device__ __forceinline__ uint32_t gtime32() { uint32_t t; asm volatile("mov.u32 %0, %globaltimer_lo;" : "=r"(t)); return t; }
#define TL(i)
#define TLDUMP(i)

struct Params {
    const __nv_bfloat16* wq[2];
    const __nv_bfloat16* x[2];
    const __nv_bfloat16* k[2];
    const __nv_bfloat16* v[2];
    const __nv_bfloat16* wo[2];
    __nv_bfloat16* out;
    uint32_t* mail;
    uint32_t* tl;
    int dt, dtw, t0, win, stag, auxgo, nap, qmode;
};

__device__ __forceinline__ uint32_t smem_u32(const void* p) { return (uint32_t)__cvta_generic_to_shared(p); }
__device__ __forceinline__ void mbar_init(uint32_t bar, uint32_t cnt) {
    asm volatile("mbarrier.init.shared::cta.b64 [%0], %1;" ::"r"(bar), "r"(cnt) : "memory");
}
__device__ __forceinline__ void mbar_expect_tx(uint32_t bar, uint32_t bytes) {
    asm volatile("mbarrier.arrive.expect_tx.shared::cta.b64 _, [%0], %1;" ::"r"(bar), "r"(bytes) : "memory");
}
__device__ __forceinline__ void mbar_arrive(uint32_t bar) {
    asm volatile("mbarrier.arrive.shared::cta.b64 _, [%0];" ::"r"(bar) : "memory");
}
__device__ __forceinline__ bool mbar_try(uint32_t bar, uint32_t parity) {
    uint32_t ok;
    asm volatile("{\n.reg .pred p;\nmbarrier.try_wait.parity.shared::cta.b64 p, [%1], %2;\nselp.u32 %0, 1, 0, p;\n}"
                 : "=r"(ok) : "r"(bar), "r"(parity) : "memory");
    return ok != 0;
}
__device__ __forceinline__ void mbar_wait(uint32_t bar, uint32_t parity) {
    unsigned n = 0;
#pragma unroll 1
    while (!mbar_try(bar, parity)) { if (++n > SPIN_LIMIT) break; }
}
__device__ __forceinline__ void bulk_g2s(uint32_t dst, const void* src, uint32_t bytes, uint32_t bar, uint64_t pol) {
    asm volatile("cp.async.bulk.shared::cluster.global.mbarrier::complete_tx::bytes.L2::cache_hint [%0], [%1], %2, [%3], %4;"
                 ::"r"(dst), "l"(src), "r"(bytes), "r"(bar), "l"(pol) : "memory");
}
__device__ __forceinline__ void expect_and_copy(uint32_t dst, const void* src, uint32_t bytes, uint32_t bar, uint64_t pol) {
    asm volatile("{\n.reg .pred p;\nelect.sync _|p, 0xffffffff;\n"
                 "@p mbarrier.arrive.expect_tx.shared::cta.b64 _, [%3], %2;\n"
                 "@p cp.async.bulk.shared::cluster.global.mbarrier::complete_tx::bytes.L2::cache_hint [%0], [%1], %2, [%3], %4;\n}"
                 ::"r"(dst), "l"(src), "r"(bytes), "r"(bar), "l"(pol) : "memory");
}
__device__ __forceinline__ void copy_elect(uint32_t dst, const void* src, uint32_t bytes, uint32_t bar, uint64_t pol) {
    asm volatile("{\n.reg .pred p;\nelect.sync _|p, 0xffffffff;\n"
                 "@p cp.async.bulk.shared::cluster.global.mbarrier::complete_tx::bytes.L2::cache_hint [%0], [%1], %2, [%3], %4;\n}"
                 ::"r"(dst), "l"(src), "r"(bytes), "r"(bar), "l"(pol) : "memory");
}
__device__ __forceinline__ void bar_sync(int id, int n) { asm volatile("bar.sync %0, %1;" ::"r"(id), "r"(n) : "memory"); }
__device__ __forceinline__ void bar_arrive(int id, int n) { asm volatile("bar.arrive %0, %1;" ::"r"(id), "r"(n) : "memory"); }

__device__ __forceinline__ uint4 lds128(uint32_t a) {
    uint4 v;
    asm volatile("ld.shared.v4.u32 {%0,%1,%2,%3}, [%4];" : "=r"(v.x), "=r"(v.y), "=r"(v.z), "=r"(v.w) : "r"(a) : "memory");
    return v;
}
__device__ __forceinline__ uint4 ldsm4t(uint32_t a) {
    uint4 v;
    asm volatile("ldmatrix.sync.aligned.m8n8.x4.trans.shared.b16 {%0,%1,%2,%3}, [%4];"
                 : "=r"(v.x), "=r"(v.y), "=r"(v.z), "=r"(v.w) : "r"(a) : "memory");
    return v;
}
__device__ __forceinline__ void mma16816(float (&c)[4], uint32_t a0, uint32_t a1, uint32_t a2, uint32_t a3, uint32_t b0, uint32_t b1) {
    asm volatile("mma.sync.aligned.m16n8k16.row.col.f32.bf16.bf16.f32 {%0,%1,%2,%3}, {%4,%5,%6,%7}, {%8,%9}, {%0,%1,%2,%3};"
                 : "+f"(c[0]), "+f"(c[1]), "+f"(c[2]), "+f"(c[3])
                 : "r"(a0), "r"(a1), "r"(a2), "r"(a3), "r"(b0), "r"(b1));
}
__device__ __forceinline__ uint32_t pack_bf16(float lo, float hi) {
    uint32_t r;
    asm("cvt.rn.bf16x2.f32 %0, %1, %2;" : "=r"(r) : "f"(hi), "f"(lo));
    return r;
}
__device__ __forceinline__ float ex2(float x) { float y; asm("ex2.approx.ftz.f32 %0, %1;" : "=f"(y) : "f"(x)); return y; }
__device__ __forceinline__ float bf_lo(uint32_t u) { return __uint_as_float(u << 16); }
__device__ __forceinline__ float bf_hi(uint32_t u) { return __uint_as_float(u & 0xffff0000u); }

__device__ __forceinline__ uint32_t enc(float f) { uint32_t u = ~__float_as_uint(f); return u ? u : 0x80000000u; }
__device__ __forceinline__ float dec(uint32_t u) { return __uint_as_float(~u); }
__device__ __forceinline__ void st_rlx(uint32_t* p, uint32_t v) { asm volatile("st.relaxed.gpu.global.u32 [%0], %1;" ::"l"(p), "r"(v) : "memory"); }
__device__ __forceinline__ void st_rlx2(uint32_t* p, uint32_t a, uint32_t b) { asm volatile("st.relaxed.gpu.global.v2.u32 [%0], {%1,%2};" ::"l"(p), "r"(a), "r"(b) : "memory"); }
__device__ __forceinline__ void st_rlx4(uint32_t* p, uint32_t a) { asm volatile("st.relaxed.gpu.global.v4.u32 [%0], {%1,%1,%1,%1};" ::"l"(p), "r"(a) : "memory"); }
__device__ __forceinline__ uint32_t ld_rlx(const uint32_t* p) { uint32_t v; asm volatile("ld.relaxed.gpu.global.u32 %0, [%1];" : "=r"(v) : "l"(p) : "memory"); return v; }
__device__ __forceinline__ uint2 ld_rlx2(const uint32_t* p) { uint2 v; asm volatile("ld.relaxed.gpu.global.v2.u32 {%0,%1}, [%2];" : "=r"(v.x), "=r"(v.y) : "l"(p) : "memory"); return v; }
__device__ __forceinline__ uint4 ld_rlx4(const uint32_t* p) { uint4 v; asm volatile("ld.relaxed.gpu.global.v4.u32 {%0,%1,%2,%3}, [%4];" : "=r"(v.x), "=r"(v.y), "=r"(v.z), "=r"(v.w) : "l"(p) : "memory"); return v; }
__device__ __forceinline__ uint32_t min4(uint4 v) { return min(min(v.x, v.y), min(v.z, v.w)); }

constexpr float SCALE_LOG2E = 0.08838834764831845f * 1.4426950408889634f;

__global__ void __launch_bounds__(NTHREADS, 1) gqa_decode_fused(const __grid_constant__ Params P) {
    extern __shared__ __align__(1024) unsigned char smem[];
    const uint32_t t_entry = gtime32();
    const int tid = threadIdx.x, warp = __shfl_sync(0xffffffffu, tid >> 5, 0), lane = tid & 31;
    const int cta = blockIdx.x;
    const int group = cta >> 2, s = cta & 3;
    const int br = group >> 4, h = group & 15;
    uint64_t pol;
    asm volatile("createpolicy.fractional.L2::evict_first.b64 %0, 1.0;" : "=l"(pol));

    uint32_t sb;
    asm volatile("mov.u32 %0, %1;" : "=r"(sb) : "r"(smem_u32(smem)));
    const int g = lane >> 2, t = lane & 3;
    const uint32_t bar_full = sb + SM_BAR, bar_empty = bar_full + NS * 8, bar_wq = bar_empty + NS * 8;
    float* red = reinterpret_cast<float*>(smem + SM_RED);
    uint32_t* const qbox = P.mail;
    uint32_t* const obox = P.mail + QBOX_WORDS;
    uint32_t* const rbox = P.mail + QBOX_WORDS + OBOX_WORDS;

    if (warp < 8) {
        const int row0 = s * QROWS_PER_CTA + warp * QROWS_PER_WARP;
        const __nv_bfloat16* wq = P.wq[br] + (size_t)row0 * QCOLS + h * 256;
#pragma unroll
        for (int i = 0; i < 3; i++) {
            const int ln = lane + 32 * i;
            if ((P.qmode & 1) && ln < QROWS_PER_WARP * 4)
                asm volatile("prefetch.global.L2 [%0];" ::"l"(wq + (size_t)(ln >> 2) * QCOLS + (ln & 3) * 64));
        }
        const uint32_t wsm = sb + SM_WQ + warp * (QROWS_PER_WARP * 512);
        if (lane == 0) {
            mbar_init(bar_wq + warp * 8, 1);
            asm volatile("fence.proxy.async.shared::cta;" ::: "memory");
            mbar_expect_tx(bar_wq + warp * 8, QROWS_PER_WARP * 512);
        }
        __syncwarp();
#pragma unroll
        for (int i = 0; i < QROWS_PER_WARP; i++) copy_elect(wsm + i * 512, wq + (size_t)i * QCOLS, 512, bar_wq + warp * 8, pol);
        const float xv = __bfloat162float(P.x[br][row0 + (lane < QROWS_PER_WARP ? lane : 0)]);
        uint32_t* qin = qbox + cta * NSPLIT * 256 + tid;
        uint32_t qu[NSPLIT];
#pragma unroll
        for (int d = 0; d < NSPLIT; d++) qu[d] = (d == s || warp != 0) ? 0u : ld_rlx(qin + d * 256);
        if (tid == 0) { TL(12); }
        mbar_wait(bar_wq + warp * 8, 0);
        float a[8];
#pragma unroll
        for (int j = 0; j < 8; j++) a[j] = 0.f;
#pragma unroll 6
        for (int i = 0; i < QROWS_PER_WARP; i++) {
            const uint4 w = lds128(wsm + i * 512 + lane * 16);
            const float xi = __shfl_sync(0xffffffffu, xv, i);
            a[0] = fmaf(xi, bf_lo(w.x), a[0]); a[1] = fmaf(xi, bf_hi(w.x), a[1]);
            a[2] = fmaf(xi, bf_lo(w.y), a[2]); a[3] = fmaf(xi, bf_hi(w.y), a[3]);
            a[4] = fmaf(xi, bf_lo(w.z), a[4]); a[5] = fmaf(xi, bf_hi(w.z), a[5]);
            a[6] = fmaf(xi, bf_lo(w.w), a[6]); a[7] = fmaf(xi, bf_hi(w.w), a[7]);
        }
        float4* dst = reinterpret_cast<float4*>(red + warp * 256 + lane * 8);
        dst[0] = make_float4(a[0], a[1], a[2], a[3]);
        dst[1] = make_float4(a[4], a[5], a[6], a[7]);
        bar_arrive(4, 288);
        bar_sync(1, 288);
        if (tid == 0) { TL(1); }
        {
            float part = 0.f;
#pragma unroll
            for (int w8 = 0; w8 < 8; w8++) part += red[w8 * 256 + tid];
            const uint32_t qe = enc(part);
#pragma unroll
            for (int d = 1; d < NSPLIT; d++) st_rlx(qbox + ((group * 4 + (s ^ d)) * NSPLIT + s) * 256 + tid, qe);
            unsigned n = 0;
#pragma unroll
            for (int d = 0; d < NSPLIT; d++) qu[d] = (s == d) ? qe : qu[d];
            if (warp != 0) bar_sync(5, 256);
#pragma unroll 1
            while (min(min(qu[0], qu[1]), min(qu[2], qu[3])) == 0 && ++n < SPIN_LIMIT) {
#pragma unroll
                for (int d = 0; d < NSPLIT; d++) if (d != s) qu[d] = ld_rlx(qin + d * 256);
            }
            if (warp == 0) { __syncwarp(); bar_arrive(5, 256); }
#pragma unroll
            for (int d = 0; d < NSPLIT; d++) if (d != s) st_rlx(qin + d * 256, 0u);
            const float q = (dec(qu[0]) + dec(qu[1])) + (dec(qu[2]) + dec(qu[3]));
            reinterpret_cast<__nv_bfloat16*>(smem + SM_Q)[tid] = __float2bfloat16(q);
        }
        bar_sync(1, 256);
        if (tid == 0) { TL(2); }

        uint4 qf[4];
#pragma unroll
        for (int j = 0; j < 4; j++)
            qf[j] = lds128(sb + SM_Q + (g & 1) * 256 + ((4 * (j ^ (g >> 2)) + t) << 4));

        const int grp = warp >> 2, w4 = warp & 3;
        const uint32_t koffA = (w4 * 16 + g) * 256 + t * 16 + (g & 1) * 64;
        const uint32_t koffB = (w4 * 16 + g) * 256 + t * 16 + ((g & 1) ^ 1) * 64;
        const int vi = lane & 7;
        const int vkey = 8 * (lane >> 4) + ((vi < 4) ? 2 * vi : 2 * (vi - 4) + 1);
        const uint32_t voff = (w4 * 16 + vkey) * 256 + ((((lane >> 3) & 1) ^ vi) << 4);
        const int kap = (g >> 1) | ((g & 1) << 2);
        const bool valid = (t >> 1) == (g & 1);
        const uint32_t amask = (t == (kap >> 1)) ? ((kap & 1) ? 0xffff0000u : 0x0000ffffu) : 0u;

        float acc[16][4];
#pragma unroll
        for (int i = 0; i < 16; i++) { acc[i][0] = acc[i][1] = acc[i][2] = acc[i][3] = 0.f; }
        float m0 = -INFINITY, m1 = -INFINITY, l0 = 0.f, l1 = 0.f;
        int slot = 2 * grp;
        uint32_t ph = 0;
#pragma unroll 1
        for (int it = 0; it < NTILES / 2; it++) {
            const uint32_t kbase = sb + SM_RING + slot * SLOT_BYTES;
            const uint32_t vbase = kbase + SLOT_BYTES;
            mbar_wait(bar_full + slot * 8, ph);
            float sa[4] = {0.f, 0.f, 0.f, 0.f}, sc[4] = {0.f, 0.f, 0.f, 0.f};
            {
                uint4 L[4], H[4];
                L[0] = lds128(kbase + koffA);       H[0] = lds128(kbase + koffA + 2048);
                L[1] = lds128(kbase + koffB);       H[1] = lds128(kbase + koffB + 2048);
                L[2] = lds128(kbase + koffA + 128); H[2] = lds128(kbase + koffA + 128 + 2048);
                L[3] = lds128(kbase + koffB + 128); H[3] = lds128(kbase + koffB + 128 + 2048);
#pragma unroll
                for (int j = 0; j < 4; j++) {
                    mma16816(sa, L[j].x, H[j].x, L[j].y, H[j].y, qf[j].x, qf[j].y);
                    mma16816(sc, L[j].z, H[j].z, L[j].w, H[j].w, qf[j].z, qf[j].w);
                }
            }
            __syncwarp();
            if (lane == 0) mbar_arrive(bar_empty + slot * 8);
            const float s0 = valid ? sa[0] + sc[0] : -INFINITY;
            const float s1 = valid ? sa[1] + sc[1] : -INFINITY;
            const float s2 = valid ? sa[2] + sc[2] : -INFINITY;
            const float s3 = valid ? sa[3] + sc[3] : -INFINITY;
            float x0 = fmaxf(s0, s2), x1 = fmaxf(s1, s3);
#pragma unroll
            for (int o = 2; o <= 16; o <<= 1) {
                x0 = fmaxf(x0, __shfl_xor_sync(0xffffffffu, x0, o));
                x1 = fmaxf(x1, __shfl_xor_sync(0xffffffffu, x1, o));
            }
            if (x0 > m0 || x1 > m1) {
                const float n0 = fmaxf(m0, x0), n1 = fmaxf(m1, x1);
                const float a0 = ex2((m0 - n0) * SCALE_LOG2E), a1 = ex2((m1 - n1) * SCALE_LOG2E);
                m0 = n0; m1 = n1;
                l0 *= a0; l1 *= a1;
#pragma unroll
                for (int i = 0; i < 8; i++) {
                    acc[i][0] *= a0; acc[i][1] *= a0; acc[i][2] *= a0; acc[i][3] *= a0;
                    acc[8 + i][0] *= a1; acc[8 + i][1] *= a1; acc[8 + i][2] *= a1; acc[8 + i][3] *= a1;
                }
            }
            const float b0 = -m0 * SCALE_LOG2E, b1 = -m1 * SCALE_LOG2E;
            const float p0 = ex2(fmaf(s0, SCALE_LOG2E, b0)), p1 = ex2(fmaf(s1, SCALE_LOG2E, b1));
            const float p2 = ex2(fmaf(s2, SCALE_LOG2E, b0)), p3 = ex2(fmaf(s3, SCALE_LOG2E, b1));
            l0 += p0 + p2; l1 += p1 + p3;
            const uint32_t pa0 = pack_bf16(p0, p0) & amask, pa1 = pack_bf16(p1, p1) & amask;
            const uint32_t pa2 = pack_bf16(p2, p2) & amask, pa3 = pack_bf16(p3, p3) & amask;

            mbar_wait(bar_full + slot * 8 + 8, ph);
            if (tid == 128 && (it & 1)) { TL(16 + (it >> 1)); }
#pragma unroll
            for (int j = 0; j < 8; j++) {
                const uint4 a = ldsm4t(vbase + (voff ^ ((j & 3) << 5)) + (j >> 2) * 128);
                mma16816(acc[j], a.x, a.y, a.z, a.w, pa0, pa2);
                mma16816(acc[8 + j], a.x, a.y, a.z, a.w, pa1, pa3);
            }
            __syncwarp();
            if (lane == 0) mbar_arrive(bar_empty + slot * 8 + 8);
            slot += 4;
            if (slot >= NS) { slot -= NS; ph ^= 1; }
        }
        if (tid == 0) { TL(3); }
        if (tid == 128) { TL(10); }

#pragma unroll
        for (int q = 0; q < 4; q++) {
            float r[8];
#pragma unroll
            for (int y = 0; y < 8; y++) r[y] = acc[4 * q + (y >> 1)][2 * (y & 1)] + acc[4 * q + ((y ^ 4) >> 1)][2 * (y & 1) + 1];
#pragma unroll
            for (int y = 0; y < 8; y += 2) r[y] += __shfl_xor_sync(0xffffffffu, r[y + 1], 1);
            r[0] += __shfl_xor_sync(0xffffffffu, r[2], 2);
            r[4] += __shfl_xor_sync(0xffffffffu, r[6], 2);
            float* dst2 = red + warp * 256 + q * 64 + t * 8 + g;
            dst2[0] = r[0];
            dst2[32] = r[4];
        }
#pragma unroll
        for (int o = 2; o <= 16; o <<= 1) {
            l0 += __shfl_xor_sync(0xffffffffu, l0, o);
            l1 += __shfl_xor_sync(0xffffffffu, l1, o);
        }
        float* ml = reinterpret_cast<float*>(smem + SM_ML);
        if (lane == 0) *reinterpret_cast<float4*>(ml + warp * 4) = make_float4(m0, l0, m1, l1);
        bar_sync(1, 256);
        {
            const int hd = tid >> 7;
            float2 w[8];
#pragma unroll
            for (int i = 0; i < 8; i++) w[i] = *reinterpret_cast<const float2*>(ml + i * 4 + hd * 2);
            float M = w[0].x;
#pragma unroll
            for (int i = 1; i < 8; i++) M = fmaxf(M, w[i].x);
            float o = 0.f, L = 0.f;
#pragma unroll
            for (int i = 0; i < 8; i++) {
                const float f = ex2((w[i].x - M) * SCALE_LOG2E);
                o = fmaf(f, red[i * 256 + tid], o);
                L = fmaf(f, w[i].y, L);
            }
            uint32_t* box = obox + ((group * 4 + (tid >> 6)) * NSPLIT + s) * 128;
            st_rlx(box + (tid & 63), enc(o));
            if ((tid & 63) < 8) st_rlx(box + 64 + (tid & 7), enc((tid & 1) ? L : M));
        }
        if (tid == 0) { TL(4); }
    } else if (warp == 8) {
        const size_t off = ((size_t)h * SK + (size_t)s * KEYS_PER_CTA) * DH;
        const unsigned char* kp = reinterpret_cast<const unsigned char*>(P.k[br] + off);
        const unsigned char* vp = reinterpret_cast<const unsigned char*>(P.v[br] + off);
        const unsigned char* wop = reinterpret_cast<const unsigned char*>(P.wo[br] + (size_t)(h * 256 + s * 64) * D_MODEL);
        if (lane == 0) {
#pragma unroll
            for (int i = 0; i < NS; i++) { mbar_init(bar_full + i * 8, 1); mbar_init(bar_empty + i * 8, 4); }
            asm volatile("fence.proxy.async.shared::cta;" ::: "memory");
        }
        __syncwarp();
        bar_arrive(1, 288);
        if ((P.qmode & 2) && lane == 0) {
            asm volatile("cp.async.bulk.prefetch.L2.global [%0], 16;" ::"l"(kp));
            asm volatile("cp.async.bulk.prefetch.L2.global [%0], 16;" ::"l"(vp));
            asm volatile("cp.async.bulk.prefetch.L2.global [%0], 16;" ::"l"(wop));
            asm volatile("cp.async.bulk.prefetch.L2.global [%0], 16;" ::"l"(wop + 4 * WO_CHUNK_BYTES - 16));
        }
        __syncwarp();
        uint32_t tnext = t_entry + P.t0 + ((cta * P.stag) >> 7);
        const int win = P.win, dt = P.dt, dtw = P.dtw, auxgo = P.auxgo, nfree = P.nap;
        uint32_t sbar = bar_full, sdst = sb + SM_RING, wbar = bar_full;
        uint32_t eph = 1, wph = 0;
        const unsigned char* src = kp;
        const long long kv_delta = vp - kp;
#pragma unroll 1
        for (int i = 0; i < 2 * NTILES + 4; i++) {
            if (i == WQ_SLOT0) bar_sync(4, 288);
            if (i == 2 * NTILES) src = wop;
            const bool isw = i >= 2 * NTILES;
            if (i >= NS) mbar_wait(sbar + NS * 8, eph);
            if (i >= win) {
                mbar_wait(wbar, wph);
                wbar += 8;
                if (wbar == bar_empty) { wbar = bar_full; wph ^= 1; }
            }
            unsigned n = 0;
#pragma unroll 1
            while (i >= nfree && (int)(gtime32() - tnext) < 0 && ++n < SPIN_LIMIT) {}
            expect_and_copy(sdst, src, isw ? WO_CHUNK_BYTES : TILE_BYTES, sbar, pol);
            if (lane == 0 && i == 0) { TL(13); }
            tnext += isw ? dtw : dt;
            src += isw ? (long long)WO_CHUNK_BYTES : ((i & 1) ? TILE_BYTES - kv_delta : kv_delta);
            sbar += 8; sdst += SLOT_BYTES;
            if (sbar == bar_empty) { sbar = bar_full; sdst = sb + SM_RING; eph ^= 1; }
            if (i == auxgo) bar_arrive(3, 64);
        }
    } else {
        bar_sync(3, 64);
        const int lidx = cta & 63;
        const bool reducer = lidx < NRED;
        uint32_t* rin = rbox + ((br * NRED + (reducer ? lidx : 0)) * 64 + (lane >> 2)) * 16 + (lane & 3) * 4;
        uint4 r[8];
        if (reducer) {
#pragma unroll
            for (int i = 0; i < 8; i++) r[i] = ld_rlx4(rin + i * 128);
        }
        {
            uint32_t* box = obox + cta * NSPLIT * 128;
            uint2 ov[NSPLIT], mv[NSPLIT];
            unsigned n = 0;
            uint32_t z;
#pragma unroll 1
            do {
#pragma unroll
                for (int d = 0; d < NSPLIT; d++) { ov[d] = ld_rlx2(box + d * 128 + 2 * lane); mv[d] = ld_rlx2(box + d * 128 + 64); }
                z = 0xffffffffu;
#pragma unroll
                for (int d = 0; d < NSPLIT; d++) z = min(min(z, min(ov[d].x, ov[d].y)), min(mv[d].x, mv[d].y));
            } while (z == 0 && ++n < SPIN_LIMIT);
            if (lane == 0) { TL(6); }
            const float M = fmaxf(fmaxf(dec(mv[0].x), dec(mv[1].x)), fmaxf(dec(mv[2].x), dec(mv[3].x)));
            float oa = 0.f, ob = 0.f, L = 0.f;
#pragma unroll
            for (int d = 0; d < NSPLIT; d++) {
                const float f = ex2((dec(mv[d].x) - M) * SCALE_LOG2E);
                oa = fmaf(f, dec(ov[d].x), oa);
                ob = fmaf(f, dec(ov[d].y), ob);
                L = fmaf(f, dec(mv[d].y), L);
            }
            const float inv = __fdividef(1.0f, L);
            reinterpret_cast<uint32_t*>(smem + SM_O)[lane] = pack_bf16(oa * inv, ob * inv);
            __syncwarp();
            bar_arrive(2, 320);
#pragma unroll
            for (int d = 0; d < NSPLIT; d++) {
                st_rlx2(box + d * 128 + 2 * lane, 0u, 0u);
                if (lane < 4) st_rlx2(box + d * 128 + 64 + 2 * lane, 0u, 0u);
            }
        }
        if (reducer) {
            unsigned n = 0;
            uint32_t z;
#pragma unroll 1
            do {
#pragma unroll
                for (int i = 0; i < 8; i++) if (min4(r[i]) == 0) r[i] = ld_rlx4(rin + i * 128);
                z = 0xffffffffu;
#pragma unroll
                for (int i = 0; i < 8; i++) z = min(z, min4(r[i]));
            } while (z == 0 && ++n < SPIN_LIMIT);
            float a0 = 0.f, a1 = 0.f, a2 = 0.f, a3 = 0.f;
#pragma unroll
            for (int i = 0; i < 8; i++) { a0 += dec(r[i].x); a1 += dec(r[i].y); a2 += dec(r[i].z); a3 += dec(r[i].w); }
            __syncwarp();
#pragma unroll
            for (int o = 4; o <= 16; o <<= 1) {
                a0 += __shfl_xor_sync(0xffffffffu, a0, o); a1 += __shfl_xor_sync(0xffffffffu, a1, o);
                a2 += __shfl_xor_sync(0xffffffffu, a2, o); a3 += __shfl_xor_sync(0xffffffffu, a3, o);
            }
            if (lane < 8)
                *reinterpret_cast<uint32_t*>(P.out + br * D_MODEL + lidx * 16 + (lane & 4) * 2 + (lane & 3) * 2) =
                    (lane & 4) ? pack_bf16(a1, a3) : pack_bf16(a0, a2);
            if (lane == 0) { TL(9); }
#pragma unroll
            for (int i = 0; i < 8; i++) st_rlx4(rin + i * 128, 0u);
        }
        return;
    }

    {
        const int i8 = lane & 7;
        const uint32_t woff = sb + SM_WO + (8 * (lane >> 4) + i8) * WO_ROW_BYTES + warp * 128 + ((((lane >> 3) & 1) ^ i8) << 4);
        const uint32_t omask = (t == (g >> 1)) ? ((g & 1) ? 0xffff0000u : 0x0000ffffu) : 0u;
        uint32_t* rout = rbox + ((br * NRED + 4 * warp + t) * 64 + (cta & 63)) * 16 + 2 * g;
        float c[4][4];
#pragma unroll
        for (int i = 0; i < 4; i++) { c[i][0] = c[i][1] = c[i][2] = c[i][3] = 0.f; }
        uint4 wf[3][4];
#pragma unroll
        for (int ks = 0; ks < 3; ks++) {
            mbar_wait(bar_full + (WO_SLOT0 + ks) * 8, WO_PHASE);
#pragma unroll
            for (int j = 0; j < 4; j++) wf[ks][j] = ldsm4t((woff ^ (j << 5)) + ks * WO_CHUNK_BYTES);
        }
        if (tid == 0) { TL(11); }
        bar_sync(2, 320);
        const uint32_t* o32 = reinterpret_cast<const uint32_t*>(smem + SM_O);
        uint32_t of[8];
#pragma unroll
        for (int j = 0; j < 8; j++) of[j] = o32[4 * j + t] & omask;
#pragma unroll
        for (int ks = 0; ks < 3; ks++) {
#pragma unroll
            for (int j = 0; j < 4; j++)
                mma16816(c[j], wf[ks][j].x, wf[ks][j].y, wf[ks][j].z, wf[ks][j].w, of[2 * ks], of[2 * ks + 1]);
        }
        mbar_wait(bar_full + (WO_SLOT0 + 3) * 8, WO_PHASE);
        if (tid == 32) { TL(14); }
#pragma unroll
        for (int j = 0; j < 4; j++) {
            const uint4 a = ldsm4t((woff ^ (j << 5)) + 3 * WO_CHUNK_BYTES);
            mma16816(c[j], a.x, a.y, a.z, a.w, of[6], of[7]);
        }
        float r[8];
#pragma unroll
        for (int y = 0; y < 8; y++) r[y] = c[y >> 1][2 * (y & 1)] + c[y >> 1][2 * ((y ^ 1) & 1) + 1];
        r[0] += __shfl_xor_sync(0xffffffffu, r[2], 1);
        r[1] += __shfl_xor_sync(0xffffffffu, r[3], 1);
        r[4] += __shfl_xor_sync(0xffffffffu, r[6], 1);
        r[5] += __shfl_xor_sync(0xffffffffu, r[7], 1);
        r[0] += __shfl_xor_sync(0xffffffffu, r[4], 2);
        r[1] += __shfl_xor_sync(0xffffffffu, r[5], 2);
        st_rlx2(rout, enc(r[0]), enc(r[1]));
        if (tid == 0) { TL(8); }
    }
}

}

static int g_tune[8] = {655, 736, 2100, 8, 650, 62, 0, 3};

extern "C" void kernel_launch(void* const* d_in, const int* in_sizes, int n_in, void* d_out, int out_size) {
    (void)in_sizes; (void)n_in; (void)out_size;
    static uint32_t* mail = nullptr;
    if (!mail) {
        cudaFuncSetAttribute(gqa_decode_fused, cudaFuncAttributeMaxDynamicSharedMemorySize, SM_TOTAL);
        void* p = nullptr;
        cudaGetSymbolAddress(&p, g_mail);
        mail = (uint32_t*)p;
    }
    Params p;
    for (int b = 0; b < 2; b++) {
        p.x[b] = (const __nv_bfloat16*)d_in[5 * b + 0];
        p.k[b] = (const __nv_bfloat16*)d_in[5 * b + 1];
        p.v[b] = (const __nv_bfloat16*)d_in[5 * b + 2];
        p.wq[b] = (const __nv_bfloat16*)d_in[5 * b + 3];
        p.wo[b] = (const __nv_bfloat16*)d_in[5 * b + 4];
    }
    p.out = (__nv_bfloat16*)d_out;
    p.mail = mail;
    p.tl = nullptr;
    p.dt = g_tune[0]; p.dtw = g_tune[1]; p.t0 = g_tune[2]; p.win = g_tune[3]; p.stag = g_tune[4]; p.auxgo = g_tune[5]; p.nap = g_tune[6]; p.qmode = g_tune[7];
    gqa_decode_fused<<<NCTA, NTHREADS, SM_TOTAL>>>(p);
}
```

```cpp
#include <cuda.h>
#include <cuda_runtime.h>
#include <cuda_bf16.h>
#include <stdint.h>

namespace {

constexpr int D_MODEL = 576;
constexpr int HKV = 16;
constexpr int SK = 8192;
constexpr int DH = 128;
constexpr int QCOLS = 4096;
constexpr int NSPLIT = 2;
constexpr int NCTA = 2 * HKV * NSPLIT;
constexpr int TILE_KEYS = 64;
constexpr int TILE_BYTES = TILE_KEYS * DH * 2;
constexpr int NTILES = SK / NSPLIT / TILE_KEYS;
constexpr int NKV = 2 * NTILES;
constexpr int PH = 4;
constexpr int PU = PH / 2;
constexpr int NS = 12;
constexpr int WO_ROW_BYTES = D_MODEL * 2;
constexpr int WO_CHUNK_BYTES = 16 * WO_ROW_BYTES;
constexpr int WO_CHUNKS = 8;
constexpr int SLOT_BYTES = WO_CHUNK_BYTES;
constexpr int WQ_SLOT0 = NS - 8;
constexpr int QROWS_PER_CTA = D_MODEL / NSPLIT;
constexpr int NTHREADS = 352;
constexpr int NRED = 36;
constexpr int NSRC = HKV * NSPLIT;
constexpr unsigned SPIN_LIMIT = 1u << 19;

#define LAT_TARGET 1800
#define CTL_GAIN 22
constexpr int CTL_FIRST = 12, CTL_STOP = NKV - 8, CTL_NAP = 500;

constexpr int SM_RING = 0;
constexpr int SM_RED = SM_RING + NS * SLOT_BYTES;
constexpr int SM_PQ = SM_RED + 8 * 256 * 4;
constexpr int SM_PO = SM_PQ + 1024;
constexpr int SM_ML = SM_PO + 528;
constexpr int SM_Q = SM_ML + 128;
constexpr int SM_O = SM_Q;
constexpr int SM_BAR = SM_Q + 512;
constexpr int SM_CTL = SM_BAR + (2 * NS + 10) * 8;
constexpr int SM_TOTAL = SM_CTL + 80;
static_assert(SM_TOTAL <= 232448, "shared memory");

constexpr int RBOX_WORDS = 2 * NRED * NSRC * 16;
__device__ __align__(1024) uint32_t g_mail[RBOX_WORDS + 32];

struct Params {
    const __nv_bfloat16* wq[2];
    const __nv_bfloat16* x[2];
    const __nv_bfloat16* k[2];
    const __nv_bfloat16* v[2];
    const __nv_bfloat16* wo[2];
    __nv_bfloat16* out;
    uint32_t* mail;
    int dt, t0;
    CUtensorMap wq_map[2];
};

__device__ __forceinline__ uint32_t gtime32() { uint32_t t; asm volatile("mov.u32 %0, %globaltimer_lo;" : "=r"(t)); return t; }
__device__ __forceinline__ uint32_t smem_u32(const void* p) { return (uint32_t)__cvta_generic_to_shared(p); }
__device__ __forceinline__ void mbar_init(uint32_t bar, uint32_t cnt) {
    asm volatile("mbarrier.init.shared::cta.b64 [%0], %1;" ::"r"(bar), "r"(cnt) : "memory");
}
__device__ __forceinline__ void mbar_expect_tx(uint32_t bar, uint32_t bytes) {
    asm volatile("mbarrier.arrive.expect_tx.shared::cta.b64 _, [%0], %1;" ::"r"(bar), "r"(bytes) : "memory");
}
__device__ __forceinline__ void mbar_arrive(uint32_t bar) {
    asm volatile("mbarrier.arrive.shared::cta.b64 _, [%0];" ::"r"(bar) : "memory");
}
__device__ __forceinline__ void mbar_arrive_n(uint32_t bar, uint32_t n) {
    asm volatile("mbarrier.arrive.shared::cta.b64 _, [%0], %1;" ::"r"(bar), "r"(n) : "memory");
}
__device__ __forceinline__ void mbar_wait(uint32_t bar, uint32_t parity) {
    unsigned n = 0;
    uint32_t ok;
#pragma unroll 1
    do {
        asm volatile("{\n.reg .pred p;\nmbarrier.try_wait.parity.shared::cta.b64 p, [%1], %2;\nselp.u32 %0, 1, 0, p;\n}"
                     : "=r"(ok) : "r"(bar), "r"(parity) : "memory");
    } while (!ok && ++n <= SPIN_LIMIT);
}
__device__ __forceinline__ void mbar_wait_cluster(uint32_t bar, uint32_t parity) {
    unsigned n = 0;
    uint32_t ok;
#pragma unroll 1
    do {
        asm volatile("{\n.reg .pred p;\nmbarrier.try_wait.parity.acquire.cluster.shared::cta.b64 p, [%1], %2;\nselp.u32 %0, 1, 0, p;\n}"
                     : "=r"(ok) : "r"(bar), "r"(parity) : "memory");
    } while (!ok && ++n <= SPIN_LIMIT);
}
__device__ __forceinline__ void expect_and_copy(uint32_t dst, const void* src, uint32_t bytes, uint32_t bar, uint64_t pol) {
    asm volatile("{\n.reg .pred p;\nelect.sync _|p, 0xffffffff;\n"
                 "@p mbarrier.arrive.expect_tx.shared::cta.b64 _, [%3], %2;\n"
                 "@p cp.async.bulk.shared::cluster.global.mbarrier::complete_tx::bytes.L2::cache_hint [%0], [%1], %2, [%3], %4;\n}"
                 ::"r"(dst), "l"(src), "r"(bytes), "r"(bar), "l"(pol) : "memory");
}
__device__ __forceinline__ void expect_and_copy_2d(uint32_t dst, const CUtensorMap* map, int c0, int c1, uint32_t bar, uint64_t pol) {
    asm volatile("{\n.reg .pred p;\nelect.sync _|p, 0xffffffff;\n"
                 "@p mbarrier.arrive.expect_tx.shared::cta.b64 _, [%2], %6;\n"
                 "@p cp.async.bulk.tensor.2d.shared::cluster.global.mbarrier::complete_tx::bytes.L2::cache_hint [%0], [%1, {%3, %4}], [%2], %5;\n}"
                 ::"r"(dst), "l"(map), "r"(bar), "r"(c0), "r"(c1), "l"(pol), "n"(SLOT_BYTES) : "memory");
}
__device__ __forceinline__ void st_peer(uint32_t peer_addr, float v, uint32_t peer_bar) {
    asm volatile("st.async.shared::cluster.mbarrier::complete_tx::bytes.f32 [%0], %1, [%2];" ::"r"(peer_addr), "f"(v), "r"(peer_bar) : "memory");
}
__device__ __forceinline__ void bar_sync(int id, int n) { asm volatile("bar.sync %0, %1;" ::"r"(id), "r"(n) : "memory"); }
__device__ __forceinline__ void bar_arrive(int id, int n) { asm volatile("bar.arrive %0, %1;" ::"r"(id), "r"(n) : "memory"); }
__device__ __forceinline__ void cluster_arrive() { asm volatile("barrier.cluster.arrive.relaxed.aligned;" ::: "memory"); }
__device__ __forceinline__ void cluster_wait() { asm volatile("barrier.cluster.wait.acquire.aligned;" ::: "memory"); }

__device__ __forceinline__ uint4 lds128(uint32_t a) {
    uint4 v;
    asm volatile("ld.shared.v4.u32 {%0,%1,%2,%3}, [%4];" : "=r"(v.x), "=r"(v.y), "=r"(v.z), "=r"(v.w) : "r"(a) : "memory");
    return v;
}
__device__ __forceinline__ uint4 ldsm4t(uint32_t a) {
    uint4 v;
    asm volatile("ldmatrix.sync.aligned.m8n8.x4.trans.shared.b16 {%0,%1,%2,%3}, [%4];"
                 : "=r"(v.x), "=r"(v.y), "=r"(v.z), "=r"(v.w) : "r"(a) : "memory");
    return v;
}
__device__ __forceinline__ void mma16816(float (&c)[4], uint32_t a0, uint32_t a1, uint32_t a2, uint32_t a3, uint32_t b0, uint32_t b1) {
    asm volatile("mma.sync.aligned.m16n8k16.row.col.f32.bf16.bf16.f32 {%0,%1,%2,%3}, {%4,%5,%6,%7}, {%8,%9}, {%0,%1,%2,%3};"
                 : "+f"(c[0]), "+f"(c[1]), "+f"(c[2]), "+f"(c[3])
                 : "r"(a0), "r"(a1), "r"(a2), "r"(a3), "r"(b0), "r"(b1));
}
__device__ __forceinline__ uint32_t pack_bf16(float lo, float hi) {
    uint32_t r;
    asm("cvt.rn.bf16x2.f32 %0, %1, %2;" : "=r"(r) : "f"(hi), "f"(lo));
    return r;
}
__device__ __forceinline__ float ex2(float x) { float y; asm("ex2.approx.ftz.f32 %0, %1;" : "=f"(y) : "f"(x)); return y; }
__device__ __forceinline__ float bf_lo(uint32_t u) { return __uint_as_float(u << 16); }
__device__ __forceinline__ float bf_hi(uint32_t u) { return __uint_as_float(u & 0xffff0000u); }

__device__ __forceinline__ uint32_t enc(float f) { uint32_t u = ~__float_as_uint(f); return u ? u : 0x80000000u; }
__device__ __forceinline__ float dec(uint32_t u) { return __uint_as_float(~u); }
__device__ __forceinline__ void st_rlx2(uint32_t* p, uint32_t a, uint32_t b) { asm volatile("st.relaxed.gpu.global.v2.u32 [%0], {%1,%2};" ::"l"(p), "r"(a), "r"(b) : "memory"); }
__device__ __forceinline__ void st_rlx4(uint32_t* p, uint32_t a) { asm volatile("st.relaxed.gpu.global.v4.u32 [%0], {%1,%1,%1,%1};" ::"l"(p), "r"(a) : "memory"); }
__device__ __forceinline__ uint32_t ld_rlx(const uint32_t* p) { uint32_t v; asm volatile("ld.relaxed.gpu.global.u32 %0, [%1];" : "=r"(v) : "l"(p) : "memory"); return v; }
__device__ __forceinline__ uint4 ld_rlx4(const uint32_t* p) { uint4 v; asm volatile("ld.relaxed.gpu.global.v4.u32 {%0,%1,%2,%3}, [%4];" : "=r"(v.x), "=r"(v.y), "=r"(v.z), "=r"(v.w) : "l"(p) : "memory"); return v; }
__device__ __forceinline__ uint32_t min4(uint4 v) { return min(min(v.x, v.y), min(v.z, v.w)); }

constexpr float SCALE_LOG2E = 0.08838834764831845f * 1.4426950408889634f;

__global__ void __cluster_dims__(NSPLIT, 1, 1) __launch_bounds__(NTHREADS, 1) gqa_decode_fused(const __grid_constant__ Params P) {
    extern __shared__ __align__(1024) unsigned char smem[];
    const uint32_t t_entry = gtime32();
    const int tid = threadIdx.x, warp = __shfl_sync(0xffffffffu, tid >> 5, 0), lane = tid & 31;
    const int cta = blockIdx.x;
    const int group = cta >> 1, s = cta & 1;
    const int br = group >> 4, h = group & 15;

    uint32_t sb;
    asm volatile("mov.u32 %0, %1;" : "=r"(sb) : "r"(smem_u32(smem)));
    const int g = lane >> 2, t = lane & 3;
    const uint32_t bar_full = sb + SM_BAR, bar_empty = bar_full + NS * 8, bar_wq = bar_empty + NS * 8;
    const uint32_t bar_pq = bar_wq + 8 * 8, bar_po = bar_pq + 8;
    float* red = reinterpret_cast<float*>(smem + SM_RED);
    volatile uint32_t* ctl = reinterpret_cast<volatile uint32_t*>(smem + SM_CTL);
    uint32_t* const rbox = P.mail;
    unsigned long long* const cword = reinterpret_cast<unsigned long long*>(P.mail + RBOX_WORDS);
    unsigned long long cold = 0;

    if (warp < 8) {
        {
            const __nv_bfloat16* w = P.wq[br] + (size_t)(s * QROWS_PER_CTA + (tid >> 2)) * QCOLS + h * 256 + (tid & 3) * 64;
            asm volatile("prefetch.global.L2 [%0];" ::"l"(w));
            asm volatile("prefetch.global.L2 [%0];" ::"l"(w + (size_t)64 * QCOLS));
        }
        const int grp = warp >> 2, w4 = warp & 3;
        const int row0 = s * QROWS_PER_CTA + grp * 36 + w4 * 9;
        const uint32_t wsm = sb + SM_RING + (WQ_SLOT0 + grp) * SLOT_BYTES + w4 * 9 * 512;
        const uint32_t wbar = bar_wq + grp * 8;
        const int xl = lane < 27 ? lane : 0;
        const float xv = __bfloat162float(P.x[br][row0 + 72 * (xl / 9) + xl % 9]);
        const float xw = __bfloat162float(P.x[br][row0 + 216 + (lane < 9 ? lane : 0)]);
        cluster_arrive();
        bar_sync(1, 288);
        float a[8];
#pragma unroll
        for (int j = 0; j < 8; j++) a[j] = 0.f;
#pragma unroll 1
        for (int j = 0; j < 4; j++) {
            mbar_wait(wbar + j * 16, 0);
            const float xs = j < 3 ? xv : xw;
            const int xb = j < 3 ? 9 * j : 0;
#pragma unroll
            for (int i = 0; i < 9; i++) {
                const uint4 w = lds128(wsm + j * 2 * SLOT_BYTES + i * 512 + lane * 16);
                const float xi = __shfl_sync(0xffffffffu, xs, xb + i);
                a[0] = fmaf(xi, bf_lo(w.x), a[0]); a[1] = fmaf(xi, bf_hi(w.x), a[1]);
                a[2] = fmaf(xi, bf_lo(w.y), a[2]); a[3] = fmaf(xi, bf_hi(w.y), a[3]);
                a[4] = fmaf(xi, bf_lo(w.z), a[4]); a[5] = fmaf(xi, bf_hi(w.z), a[5]);
                a[6] = fmaf(xi, bf_lo(w.w), a[6]); a[7] = fmaf(xi, bf_hi(w.w), a[7]);
            }
            __syncwarp();
            if (lane == 0) mbar_arrive(bar_empty + (WQ_SLOT0 + 2 * j + grp) * 8);
        }
        float4* dst = reinterpret_cast<float4*>(red + warp * 256 + lane * 8);
        dst[0] = make_float4(a[0], a[1], a[2], a[3]);
        dst[1] = make_float4(a[4], a[5], a[6], a[7]);
        cluster_wait();
        bar_sync(1, 256);
        uint32_t peer;
        asm volatile("mapa.shared::cluster.u32 %0, %1, %2;" : "=r"(peer) : "r"(sb), "r"(s ^ 1));
        {
            float part = 0.f;
#pragma unroll
            for (int w8 = 0; w8 < 8; w8++) part += red[w8 * 256 + tid];
            st_peer(peer + SM_PQ + tid * 4, part, peer + (bar_pq - sb));
            mbar_wait_cluster(bar_pq, 0);
            reinterpret_cast<__nv_bfloat16*>(smem + SM_Q)[tid] = __float2bfloat16(part + reinterpret_cast<const float*>(smem + SM_PQ)[tid]);
        }
        bar_sync(1, 256);

        uint4 qf[4];
#pragma unroll
        for (int j = 0; j < 4; j++)
            qf[j] = lds128(sb + SM_Q + (g & 1) * 256 + ((4 * (j ^ (g >> 2)) + t) << 4));

        const uint32_t koffA = (w4 * 16 + g) * 256 + t * 16 + (g & 1) * 64;
        const uint32_t koffB = (w4 * 16 + g) * 256 + t * 16 + ((g & 1) ^ 1) * 64;
        const int vi = lane & 7;
        const int vkey = 8 * (lane >> 4) + ((vi < 4) ? 2 * vi : 2 * (vi - 4) + 1);
        const uint32_t voff = (w4 * 16 + vkey) * 256 + ((((lane >> 3) & 1) ^ vi) << 4);
        const int kap = (g >> 1) | ((g & 1) << 2);
        const bool valid = (t >> 1) == (g & 1);
        const uint32_t amask = (t == (kap >> 1)) ? ((kap & 1) ? 0xffff0000u : 0x0000ffffu) : 0u;

        float acc[16][4];
#pragma unroll
        for (int i = 0; i < 16; i++) { acc[i][0] = acc[i][1] = acc[i][2] = acc[i][3] = 0.f; }
        float m0 = -INFINITY, m1 = -INFINITY, l0 = 0.f, l1 = 0.f;
        uint32_t fbar = bar_full + grp * 8, tbase = sb + SM_RING + grp * SLOT_BYTES, ph = 0;
        auto advance = [&]() {
            __syncwarp();
            if (lane == 0) mbar_arrive(fbar + NS * 8);
            fbar += 16; tbase += 2 * SLOT_BYTES;
            if (fbar >= bar_empty) { fbar -= NS * 8; tbase -= NS * SLOT_BYTES; ph ^= 1; }
        };
        auto sample = [&](int i) {
            if ((tid & 127) == 0 && i >= CTL_FIRST && i < CTL_STOP + 4) {
                int e = (int)(gtime32() - ctl[i & 15]) - LAT_TARGET;
                e = max(min(e, 2000), -1000);
                if (i < CTL_STOP)
                    asm volatile("red.relaxed.gpu.global.add.u64 [%0], %1;" ::"l"(cword), "l"((unsigned long long)(long long)e << 32) : "memory");
                else
                    asm volatile("atom.relaxed.gpu.global.add.u64 %0, [%1], %2;" : "=l"(cold) : "l"(cword), "l"(1ull) : "memory");
            }
        };
#pragma unroll 1
        for (int it = 0; it < NTILES / PH; it++) {
            float sv[PU][4];
#pragma unroll
            for (int u = 0; u < PU; u++) {
                mbar_wait(fbar, ph);
                if (u & 1) sample(2 * PH * it + 2 * u + grp);
                float sa[4] = {0.f, 0.f, 0.f, 0.f}, sc[4] = {0.f, 0.f, 0.f, 0.f};
                uint4 L[4], H[4];
                L[0] = lds128(tbase + koffA);       H[0] = lds128(tbase + koffA + 2048);
                L[1] = lds128(tbase + koffB);       H[1] = lds128(tbase + koffB + 2048);
                L[2] = lds128(tbase + koffA + 128); H[2] = lds128(tbase + koffA + 128 + 2048);
                L[3] = lds128(tbase + koffB + 128); H[3] = lds128(tbase + koffB + 128 + 2048);
#pragma unroll
                for (int j = 0; j < 4; j++) {
                    mma16816(sa, L[j].x, H[j].x, L[j].y, H[j].y, qf[j].x, qf[j].y);
                    mma16816(sc, L[j].z, H[j].z, L[j].w, H[j].w, qf[j].z, qf[j].w);
                }
                advance();
#pragma unroll
                for (int e = 0; e < 4; e++) sv[u][e] = valid ? sa[e] + sc[e] : -INFINITY;
            }
            float x0 = fmaxf(sv[0][0], sv[0][2]), x1 = fmaxf(sv[0][1], sv[0][3]);
#pragma unroll
            for (int u = 1; u < PU; u++) { x0 = fmaxf(x0, fmaxf(sv[u][0], sv[u][2])); x1 = fmaxf(x1, fmaxf(sv[u][1], sv[u][3])); }
#pragma unroll
            for (int o = 2; o <= 16; o <<= 1) {
                x0 = fmaxf(x0, __shfl_xor_sync(0xffffffffu, x0, o));
                x1 = fmaxf(x1, __shfl_xor_sync(0xffffffffu, x1, o));
            }
            if (x0 > m0 || x1 > m1) {
                const float n0 = fmaxf(m0, x0), n1 = fmaxf(m1, x1);
                const float a0 = ex2((m0 - n0) * SCALE_LOG2E), a1 = ex2((m1 - n1) * SCALE_LOG2E);
                m0 = n0; m1 = n1;
                l0 *= a0; l1 *= a1;
#pragma unroll
                for (int i = 0; i < 8; i++) {
                    acc[i][0] *= a0; acc[i][1] *= a0; acc[i][2] *= a0; acc[i][3] *= a0;
                    acc[8 + i][0] *= a1; acc[8 + i][1] *= a1; acc[8 + i][2] *= a1; acc[8 + i][3] *= a1;
                }
            }
            uint32_t pb[PU][4];
#pragma unroll
            for (int u = 0; u < PU; u++) {
                const float p0 = ex2((sv[u][0] - m0) * SCALE_LOG2E), p1 = ex2((sv[u][1] - m1) * SCALE_LOG2E);
                const float p2 = ex2((sv[u][2] - m0) * SCALE_LOG2E), p3 = ex2((sv[u][3] - m1) * SCALE_LOG2E);
                l0 += p0 + p2; l1 += p1 + p3;
                pb[u][0] = pack_bf16(p0, p0) & amask; pb[u][1] = pack_bf16(p1, p1) & amask;
                pb[u][2] = pack_bf16(p2, p2) & amask; pb[u][3] = pack_bf16(p3, p3) & amask;
            }
#pragma unroll
            for (int u = 0; u < PU; u++) {
                mbar_wait(fbar, ph);
                if (u & 1) sample(2 * PH * it + PH + 2 * u + grp);
#pragma unroll
                for (int j = 0; j < 8; j++) {
                    const uint4 a = ldsm4t(tbase + (voff ^ ((j & 3) << 5)) + (j >> 2) * 128);
                    mma16816(acc[j], a.x, a.y, a.z, a.w, pb[u][0], pb[u][2]);
                    mma16816(acc[8 + j], a.x, a.y, a.z, a.w, pb[u][1], pb[u][3]);
                }
                advance();
            }
        }

#pragma unroll
        for (int q = 0; q < 4; q++) {
            float r[8];
#pragma unroll
            for (int y = 0; y < 8; y++) r[y] = acc[4 * q + (y >> 1)][2 * (y & 1)] + acc[4 * q + ((y ^ 4) >> 1)][2 * (y & 1) + 1];
#pragma unroll
            for (int y = 0; y < 8; y += 2) r[y] += __shfl_xor_sync(0xffffffffu, r[y + 1], 1);
            r[0] += __shfl_xor_sync(0xffffffffu, r[2], 2);
            r[4] += __shfl_xor_sync(0xffffffffu, r[6], 2);
            float* dst2 = red + warp * 256 + q * 64 + t * 8 + g;
            dst2[0] = r[0];
            dst2[32] = r[4];
        }
#pragma unroll
        for (int o = 2; o <= 16; o <<= 1) {
            l0 += __shfl_xor_sync(0xffffffffu, l0, o);
            l1 += __shfl_xor_sync(0xffffffffu, l1, o);
        }
        float* ml = reinterpret_cast<float*>(smem + SM_ML);
        if (lane == 0) *reinterpret_cast<float4*>(ml + warp * 4) = make_float4(m0, l0, m1, l1);
        bar_sync(1, 256);
        {
            const int hd = tid >> 7;
            float2 w[8];
#pragma unroll
            for (int i = 0; i < 8; i++) w[i] = *reinterpret_cast<const float2*>(ml + i * 4 + hd * 2);
            float M = w[0].x;
#pragma unroll
            for (int i = 1; i < 8; i++) M = fmaxf(M, w[i].x);
            float o = 0.f, L = 0.f;
#pragma unroll
            for (int i = 0; i < 8; i++) {
                const float f = ex2((w[i].x - M) * SCALE_LOG2E);
                o = fmaf(f, red[i * 256 + tid], o);
                L = fmaf(f, w[i].y, L);
            }
            const int d = tid & 127;
            if (hd != s) {
                st_peer(peer + SM_PO + d * 4, o, peer + (bar_po - sb));
                if (d < 2) st_peer(peer + SM_PO + 512 + d * 4, d ? L : M, peer + (bar_po - sb));
            } else {
                mbar_wait_cluster(bar_po, 0);
                const float* pbuf = reinterpret_cast<const float*>(smem + SM_PO);
                const float Mp = pbuf[128], Lp = pbuf[129];
                const float Mx = fmaxf(M, Mp);
                const float f = ex2((M - Mx) * SCALE_LOG2E), fp = ex2((Mp - Mx) * SCALE_LOG2E);
                reinterpret_cast<__nv_bfloat16*>(smem + SM_O)[d] = __float2bfloat16(__fdividef(f * o + fp * pbuf[d], f * L + fp * Lp));
            }
        }
    } else if (warp == 8) {
        if (lane == 0) {
            asm volatile("prefetch.param.tensormap [%0];" ::"l"(__cvta_generic_to_grid_constant(&P.wq_map[br])) : "memory");
#pragma unroll
            for (int i = 0; i < 8; i++) mbar_init(bar_wq + i * 8, 1);
        }
        __syncwarp();
        uint64_t pol;
        asm volatile("createpolicy.fractional.L2::evict_first.b64 %0, 1.0;" : "=l"(pol));
#pragma unroll
        for (int c = 0; c < 4; c++)
            expect_and_copy_2d(sb + SM_RING + (WQ_SLOT0 + c) * SLOT_BYTES, &P.wq_map[br], h * 256, s * QROWS_PER_CTA + c * 36, bar_wq + c * 8, pol);
        if (lane == 0) {
#pragma unroll
            for (int i = 0; i < 2 * NS; i++) mbar_init(bar_full + i * 8, i >= NS ? 4 : 1);
            mbar_init(bar_pq, 1);
            mbar_init(bar_po, 1);
            asm volatile("fence.mbarrier_init.release.cluster;" ::: "memory");
            mbar_expect_tx(bar_pq, 256 * 4);
            mbar_expect_tx(bar_po, 130 * 4);
#pragma unroll
            for (int i = 0; i < WQ_SLOT0; i++) mbar_arrive_n(bar_empty + i * 8, 4);
            ctl[16] = 0; ctl[17] = 0;
        }
        __syncwarp();
        cluster_arrive();
        bar_arrive(1, 288);
        bar_arrive(3, 96);
#pragma unroll
        for (int c = 4; c < 8; c++)
            expect_and_copy_2d(sb + SM_RING + (WQ_SLOT0 + c) * SLOT_BYTES, &P.wq_map[br], h * 256, s * QROWS_PER_CTA + c * 36, bar_wq + c * 8, pol);
        const size_t off = (size_t)h * SK * DH + (size_t)s * 8 * TILE_KEYS * DH;
        const unsigned char* kp = reinterpret_cast<const unsigned char*>(P.k[br] + off);
        const unsigned char* vp = reinterpret_cast<const unsigned char*>(P.v[br] + off);
        const unsigned char* wop = reinterpret_cast<const unsigned char*>(P.wo[br] + (size_t)(h * 256 + s * 128) * D_MODEL);
        if (lane == 0) {
            asm volatile("cp.async.bulk.prefetch.L2.global [%0], 16;" ::"l"(kp));
            asm volatile("cp.async.bulk.prefetch.L2.global [%0], 16;" ::"l"(vp));
            asm volatile("cp.async.bulk.prefetch.L2.global [%0], 16;" ::"l"(wop));
            asm volatile("cp.async.bulk.prefetch.L2.global [%0], 16;" ::"l"(wop + WO_CHUNKS * WO_CHUNK_BYTES - 16));
        }
        __syncwarp();
        const int dt = P.dt, dtw = dt + (dt >> 3);
        uint32_t tnext = 2 * P.t0 + ((cta * dt) >> 6);
        uint32_t sbar = bar_full, sdst = sb + SM_RING, eph = 0;
#pragma unroll 1
        for (int i = 0; i < NKV + WO_CHUNKS; i++) {
            const bool isw = i >= NKV;
            const int j = (i / (2 * PH)) * PH + (i % PH);
            const unsigned char* src = isw ? wop + (i - NKV) * WO_CHUNK_BYTES
                                           : (((i / PH) & 1) ? vp : kp) + (((j >> 3) << 4) + (j & 7)) * TILE_BYTES;
            mbar_wait(sbar + NS * 8, eph);
            unsigned n = 0;
            uint32_t now;
            const uint32_t due = t_entry + (tnext >> 1);
#pragma unroll 1
            do { now = gtime32(); } while ((int)(now - due - ctl[16]) < 0 && ++n < SPIN_LIMIT);
            if (lane == 0) ctl[i & 15] = now;
            expect_and_copy(sdst, src, isw ? WO_CHUNK_BYTES : TILE_BYTES, sbar, pol);
            tnext += isw ? dtw : dt;
            sbar += 8; sdst += SLOT_BYTES;
            if (sbar == bar_empty) { sbar = bar_full; sdst = sb + SM_RING; eph ^= 1; }
            if (i == CTL_STOP && lane == 0) ctl[17] = 1;
        }
        cluster_wait();
    } else {
        cluster_arrive();
        bar_sync(3, 96);
        cluster_wait();
        {
            unsigned n = 0;
#pragma unroll 1
            while (ctl[17] == 0 && ++n < SPIN_LIMIT) {
                __nanosleep(CTL_NAP);
                if (warp == 9) {
                    const int sum = (int)ld_rlx(reinterpret_cast<const uint32_t*>(cword) + 1);
                    if (lane == 0) ctl[16] = (uint32_t)(((sum >> 6) * CTL_GAIN) >> 8);
                }
            }
        }
        const int ridx = 2 * (cta & (NSRC - 1)) + (warp - 9);
        if (ridx < NRED) {
            uint32_t* rin = rbox + ((br * NRED + ridx) * NSRC + (lane >> 2)) * 16 + (lane & 3) * 4;
            uint32_t* outp = reinterpret_cast<uint32_t*>(P.out + br * D_MODEL + ridx * 16) + (lane & 7);
            const bool hi = lane & 4;
            uint4 r[4];
            unsigned n = 0;
#pragma unroll 1
            do {
#pragma unroll
                for (int i = 0; i < 4; i++) r[i] = ld_rlx4(rin + i * 128);
                if (n == 0) bar_sync(3 + warp, 64);
            } while (min(min(min4(r[0]), min4(r[1])), min(min4(r[2]), min4(r[3]))) == 0 && ++n < SPIN_LIMIT);
            __syncwarp();
            const float a0 = (dec(r[0].x) + dec(r[1].x)) + (dec(r[2].x) + dec(r[3].x));
            const float a1 = (dec(r[0].y) + dec(r[1].y)) + (dec(r[2].y) + dec(r[3].y));
            const float a2 = (dec(r[0].z) + dec(r[1].z)) + (dec(r[2].z) + dec(r[3].z));
            const float a3 = (dec(r[0].w) + dec(r[1].w)) + (dec(r[2].w) + dec(r[3].w));
            float lo = (hi ? a1 : a0) + __shfl_xor_sync(0xffffffffu, hi ? a0 : a1, 4);
            float up = (hi ? a3 : a2) + __shfl_xor_sync(0xffffffffu, hi ? a2 : a3, 4);
            lo += __shfl_xor_sync(0xffffffffu, lo, 8);  up += __shfl_xor_sync(0xffffffffu, up, 8);
            lo += __shfl_xor_sync(0xffffffffu, lo, 16); up += __shfl_xor_sync(0xffffffffu, up, 16);
            if (lane < 8) *outp = pack_bf16(lo, up);
#pragma unroll
            for (int i = 0; i < 4; i++) st_rlx4(rin + i * 128, 0u);
        }
        return;
    }

    {
        const int i8 = lane & 7;
        const uint32_t woff = sb + SM_RING + (8 * (lane >> 4) + i8) * WO_ROW_BYTES + warp * 128 + ((((lane >> 3) & 1) ^ i8) << 4);
        const uint32_t omask = (t == (g >> 1)) ? ((g & 1) ? 0xffff0000u : 0x0000ffffu) : 0u;
        uint32_t* rout = rbox + ((br * NRED + 4 * warp + t) * NSRC + (cta & (NSRC - 1))) * 16 + 2 * g;
        float c[4][4], c2[4][4];
#pragma unroll
        for (int i = 0; i < 4; i++) { c[i][0] = c[i][1] = c[i][2] = c[i][3] = 0.f; c2[i][0] = c2[i][1] = c2[i][2] = c2[i][3] = 0.f; }
        bar_sync(2, 288);
        const uint32_t* o32 = reinterpret_cast<const uint32_t*>(smem + SM_O);
        uint32_t ob[2 * WO_CHUNKS];
#pragma unroll
        for (int j = 0; j < 2 * WO_CHUNKS; j++) ob[j] = o32[4 * j + t] & omask;
#pragma unroll
        for (int ks = 0; ks < WO_CHUNKS - 2; ks += 2) {
            mbar_wait(bar_full + ((NKV + ks) % NS) * 8, ((NKV + ks) / NS) & 1);
            mbar_wait(bar_full + ((NKV + ks + 1) % NS) * 8, ((NKV + ks + 1) / NS) & 1);
            uint4 a[8];
#pragma unroll
            for (int j = 0; j < 8; j++) a[j] = ldsm4t((woff ^ ((j & 3) << 5)) + ((NKV + ks + (j >> 2)) % NS) * SLOT_BYTES);
#pragma unroll
            for (int j = 0; j < 4; j++) {
                mma16816(c[j], a[j].x, a[j].y, a[j].z, a[j].w, ob[2 * ks], ob[2 * ks + 1]);
                mma16816(c2[j], a[4 + j].x, a[4 + j].y, a[4 + j].z, a[4 + j].w, ob[2 * ks + 2], ob[2 * ks + 3]);
            }
        }
        if (warp < 2 && 2 * (cta & (NSRC - 1)) + warp < NRED) bar_arrive(12 + warp, 64);
#pragma unroll
        for (int ks = WO_CHUNKS - 2; ks < WO_CHUNKS; ks++) {
            mbar_wait(bar_full + ((NKV + ks) % NS) * 8, ((NKV + ks) / NS) & 1);
#pragma unroll
            for (int j = 0; j < 4; j++) {
                const uint4 a = ldsm4t((woff ^ (j << 5)) + ((NKV + ks) % NS) * SLOT_BYTES);
                if (ks & 1) mma16816(c[j], a.x, a.y, a.z, a.w, ob[2 * ks], ob[2 * ks + 1]);
                else mma16816(c2[j], a.x, a.y, a.z, a.w, ob[2 * ks], ob[2 * ks + 1]);
            }
            if (ks == WO_CHUNKS - 2) {
#pragma unroll
                for (int j = 0; j < 4; j++) { c[j][0] += c2[j][0]; c[j][1] += c2[j][1]; c[j][2] += c2[j][2]; c[j][3] += c2[j][3]; }
            }
        }
        float r[8];
#pragma unroll
        for (int y = 0; y < 8; y++) r[y] = c[y >> 1][2 * (y & 1)] + c[y >> 1][2 * ((y ^ 1) & 1) + 1];
        r[0] += __shfl_xor_sync(0xffffffffu, r[2], 1);
        r[1] += __shfl_xor_sync(0xffffffffu, r[3], 1);
        r[4] += __shfl_xor_sync(0xffffffffu, r[6], 1);
        r[5] += __shfl_xor_sync(0xffffffffu, r[7], 1);
        r[0] += __shfl_xor_sync(0xffffffffu, r[4], 2);
        r[1] += __shfl_xor_sync(0xffffffffu, r[5], 2);
        st_rlx2(rout, enc(r[0]), enc(r[1]));
        if ((uint32_t)cold == 2 * NCTA - 1)
            asm volatile("st.relaxed.gpu.global.u64 [%0], %1;" ::"l"(cword), "l"(0ull) : "memory");
    }
}

}

extern "C" void kernel_launch(void* const* d_in, const int* in_sizes, int n_in, void* d_out, int out_size) {
    (void)in_sizes; (void)n_in; (void)out_size;
    typedef CUresult (*EncodeFn)(CUtensorMap*, CUtensorMapDataType, cuuint32_t, void*, const cuuint64_t*, const cuuint64_t*,
                                 const cuuint32_t*, const cuuint32_t*, CUtensorMapInterleave, CUtensorMapSwizzle,
                                 CUtensorMapL2promotion, CUtensorMapFloatOOBfill);
    static EncodeFn encode = nullptr;
    static uint32_t* mail = nullptr;
    static int dt = 655;
    if (!mail) {
        cudaFuncSetAttribute(gqa_decode_fused, cudaFuncAttributeMaxDynamicSharedMemorySize, SM_TOTAL);
        void* p = nullptr;
        cudaGetSymbolAddress(&p, g_mail);
        mail = (uint32_t*)p;
        cudaDriverEntryPointQueryResult qres;
        cudaGetDriverEntryPoint("cuTensorMapEncodeTiled", &p, cudaEnableDefault, &qres);
        encode = (EncodeFn)p;
        int dev = 0, khz = 0, bits = 0;
        cudaGetDevice(&dev);
        if (cudaDeviceGetAttribute(&khz, cudaDevAttrMemoryClockRate, dev) == cudaSuccess &&
            cudaDeviceGetAttribute(&bits, cudaDevAttrGlobalMemoryBusWidth, dev) == cudaSuccess && khz > 0 && bits > 0) {
            const double bytes_per_ns = 2.0 * khz * 1e-6 * bits / 8.0;
            dt = (int)(2.0 * NCTA * TILE_BYTES / (0.955 * bytes_per_ns) + 0.5);
        }
        (void)cudaGetLastError();
    }
    Params p;
    for (int b = 0; b < 2; b++) {
        p.x[b] = (const __nv_bfloat16*)d_in[5 * b + 0];
        p.k[b] = (const __nv_bfloat16*)d_in[5 * b + 1];
        p.v[b] = (const __nv_bfloat16*)d_in[5 * b + 2];
        p.wq[b] = (const __nv_bfloat16*)d_in[5 * b + 3];
        p.wo[b] = (const __nv_bfloat16*)d_in[5 * b + 4];
        const cuuint64_t dims[2] = {(cuuint64_t)QCOLS, (cuuint64_t)D_MODEL};
        const cuuint64_t strides[1] = {(cuuint64_t)QCOLS * 2};
        const cuuint32_t box[2] = {256, 36}, estr[2] = {1, 1};
        encode(&p.wq_map[b], CU_TENSOR_MAP_DATA_TYPE_BFLOAT16, 2, d_in[5 * b + 3], dims, strides, box, estr,
               CU_TENSOR_MAP_INTERLEAVE_NONE, CU_TENSOR_MAP_SWIZZLE_NONE, CU_TENSOR_MAP_L2_PROMOTION_NONE,
               CU_TENSOR_MAP_FLOAT_OOB_FILL_NONE);
    }
    p.out = (__nv_bfloat16*)d_out;
    p.mail = mail;
    p.dt = dt;
    p.t0 = dt * 9 / 2 - 850;
    gqa_decode_fused<<<NCTA, NTHREADS, SM_TOTAL>>>(p);
}
```

```cpp
#include <cuda.h>
#include <cuda_runtime.h>
#include <cuda_bf16.h>
#include <stdint.h>

namespace {

constexpr int D_MODEL = 576;
constexpr int HKV = 16;
constexpr int SK = 8192;
constexpr int DH = 128;
constexpr int QCOLS = 4096;
constexpr int NSPLIT = 2;
constexpr int NCTA = 2 * HKV * NSPLIT;
constexpr int TILE_KEYS = 64;
constexpr int TILE_BYTES = TILE_KEYS * DH * 2;
constexpr int NTILES = SK / NSPLIT / TILE_KEYS;
constexpr int NKV = 2 * NTILES;
constexpr int PH = 4;
constexpr int PU = PH / 2;
constexpr int NS = 12;
constexpr int WO_ROW_BYTES = D_MODEL * 2;
constexpr int WO_CHUNK_BYTES = 16 * WO_ROW_BYTES;
constexpr int WO_CHUNKS = 8;
constexpr int SLOT_BYTES = WO_CHUNK_BYTES;
constexpr int WQ_SLOT0 = NS - 8;
constexpr int QROWS_PER_CTA = D_MODEL / NSPLIT;
constexpr int NTHREADS = 352;
constexpr int NRED = 36;
constexpr int NSRC = HKV * NSPLIT;
constexpr unsigned SPIN_LIMIT = 1u << 19;

#define LAT_TARGET 1800
#define CTL_GAIN 22
#define PFN 3
#define T0_LEAD 900
constexpr int CTL_FIRST = 12, CTL_STOP = NKV - 8, CTL_NAP = 500;

constexpr int SM_RING = 0;
constexpr int SM_RED = SM_RING + NS * SLOT_BYTES;
constexpr int SM_PQ = SM_RED + 8 * 256 * 4;
constexpr int SM_PO = SM_PQ + 1024;
constexpr int SM_ML = SM_PO + 528;
constexpr int SM_Q = SM_ML + 128;
constexpr int SM_O = SM_Q;
constexpr int SM_BAR = SM_Q + 512;
constexpr int SM_CTL = SM_BAR + (2 * NS + 10) * 8;
constexpr int SM_TOTAL = SM_CTL + 80;
static_assert(SM_TOTAL <= 232448, "shared memory");

constexpr int RBOX_WORDS = 2 * NRED * NSRC * 16;
__device__ __align__(1024) uint32_t g_mail[RBOX_WORDS + 32];

struct Params {
    const __nv_bfloat16* wq[2];
    const __nv_bfloat16* x[2];
    const __nv_bfloat16* k[2];
    const __nv_bfloat16* v[2];
    const __nv_bfloat16* wo[2];
    __nv_bfloat16* out;
    uint32_t* mail;
    int dt, t0;
    CUtensorMap wq_map[2];
};

__device__ __forceinline__ uint32_t gtime32() { uint32_t t; asm volatile("mov.u32 %0, %globaltimer_lo;" : "=r"(t)); return t; }
__device__ __forceinline__ uint32_t smem_u32(const void* p) { return (uint32_t)__cvta_generic_to_shared(p); }
__device__ __forceinline__ void mbar_init(uint32_t bar, uint32_t cnt) {
    asm volatile("mbarrier.init.shared::cta.b64 [%0], %1;" ::"r"(bar), "r"(cnt) : "memory");
}
__device__ __forceinline__ void mbar_expect_tx(uint32_t bar, uint32_t bytes) {
    asm volatile("mbarrier.arrive.expect_tx.shared::cta.b64 _, [%0], %1;" ::"r"(bar), "r"(bytes) : "memory");
}
__device__ __forceinline__ void mbar_arrive(uint32_t bar) {
    asm volatile("mbarrier.arrive.shared::cta.b64 _, [%0];" ::"r"(bar) : "memory");
}
__device__ __forceinline__ void mbar_arrive_n(uint32_t bar, uint32_t n) {
    asm volatile("mbarrier.arrive.shared::cta.b64 _, [%0], %1;" ::"r"(bar), "r"(n) : "memory");
}
__device__ __forceinline__ void mbar_wait(uint32_t bar, uint32_t parity) {
    unsigned n = 0;
    uint32_t ok;
#pragma unroll 1
    do {
        asm volatile("{\n.reg .pred p;\nmbarrier.try_wait.parity.shared::cta.b64 p, [%1], %2;\nselp.u32 %0, 1, 0, p;\n}"
                     : "=r"(ok) : "r"(bar), "r"(parity) : "memory");
    } while (!ok && ++n <= SPIN_LIMIT);
}
__device__ __forceinline__ void mbar_wait_cluster(uint32_t bar, uint32_t parity) {
    unsigned n = 0;
    uint32_t ok;
#pragma unroll 1
    do {
        asm volatile("{\n.reg .pred p;\nmbarrier.try_wait.parity.acquire.cluster.shared::cta.b64 p, [%1], %2;\nselp.u32 %0, 1, 0, p;\n}"
                     : "=r"(ok) : "r"(bar), "r"(parity) : "memory");
    } while (!ok && ++n <= SPIN_LIMIT);
}
__device__ __forceinline__ void expect_and_copy(uint32_t dst, const void* src, uint32_t bytes, uint32_t bar, uint64_t pol) {
    asm volatile("{\n.reg .pred p;\nelect.sync _|p, 0xffffffff;\n"
                 "@p mbarrier.arrive.expect_tx.shared::cta.b64 _, [%3], %2;\n"
                 "@p cp.async.bulk.shared::cluster.global.mbarrier::complete_tx::bytes.L2::cache_hint [%0], [%1], %2, [%3], %4;\n}"
                 ::"r"(dst), "l"(src), "r"(bytes), "r"(bar), "l"(pol) : "memory");
}
__device__ __forceinline__ void expect_and_copy_2d(uint32_t dst, const CUtensorMap* map, int c0, int c1, uint32_t bar, uint64_t pol) {
    asm volatile("{\n.reg .pred p;\nelect.sync _|p, 0xffffffff;\n"
                 "@p mbarrier.arrive.expect_tx.shared::cta.b64 _, [%2], %6;\n"
                 "@p cp.async.bulk.tensor.2d.shared::cluster.global.mbarrier::complete_tx::bytes.L2::cache_hint [%0], [%1, {%3, %4}], [%2], %5;\n}"
                 ::"r"(dst), "l"(map), "r"(bar), "r"(c0), "r"(c1), "l"(pol), "n"(SLOT_BYTES) : "memory");
}
__device__ __forceinline__ void st_peer(uint32_t peer_addr, float v, uint32_t peer_bar) {
    asm volatile("st.async.shared::cluster.mbarrier::complete_tx::bytes.f32 [%0], %1, [%2];" ::"r"(peer_addr), "f"(v), "r"(peer_bar) : "memory");
}
__device__ __forceinline__ void bar_sync(int id, int n) { asm volatile("bar.sync %0, %1;" ::"r"(id), "r"(n) : "memory"); }
__device__ __forceinline__ void bar_arrive(int id, int n) { asm volatile("bar.arrive %0, %1;" ::"r"(id), "r"(n) : "memory"); }
__device__ __forceinline__ void cluster_arrive() { asm volatile("barrier.cluster.arrive.relaxed.aligned;" ::: "memory"); }
__device__ __forceinline__ void cluster_wait() { asm volatile("barrier.cluster.wait.acquire.aligned;" ::: "memory"); }

__device__ __forceinline__ uint4 lds128(uint32_t a) {
    uint4 v;
    asm volatile("ld.shared.v4.u32 {%0,%1,%2,%3}, [%4];" : "=r"(v.x), "=r"(v.y), "=r"(v.z), "=r"(v.w) : "r"(a) : "memory");
    return v;
}
__device__ __forceinline__ uint4 ldsm4t(uint32_t a) {
    uint4 v;
    asm volatile("ldmatrix.sync.aligned.m8n8.x4.trans.shared.b16 {%0,%1,%2,%3}, [%4];"
                 : "=r"(v.x), "=r"(v.y), "=r"(v.z), "=r"(v.w) : "r"(a) : "memory");
    return v;
}
__device__ __forceinline__ void mma16816(float (&c)[4], uint32_t a0, uint32_t a1, uint32_t a2, uint32_t a3, uint32_t b0, uint32_t b1) {
    asm volatile("mma.sync.aligned.m16n8k16.row.col.f32.bf16.bf16.f32 {%0,%1,%2,%3}, {%4,%5,%6,%7}, {%8,%9}, {%0,%1,%2,%3};"
                 : "+f"(c[0]), "+f"(c[1]), "+f"(c[2]), "+f"(c[3])
                 : "r"(a0), "r"(a1), "r"(a2), "r"(a3), "r"(b0), "r"(b1));
}
__device__ __forceinline__ uint32_t pack_bf16(float lo, float hi) {
    uint32_t r;
    asm("cvt.rn.bf16x2.f32 %0, %1, %2;" : "=r"(r) : "f"(hi), "f"(lo));
    return r;
}
__device__ __forceinline__ float ex2(float x) { float y; asm("ex2.approx.ftz.f32 %0, %1;" : "=f"(y) : "f"(x)); return y; }
__device__ __forceinline__ float bf_lo(uint32_t u) { return __uint_as_float(u << 16); }
__device__ __forceinline__ float bf_hi(uint32_t u) { return __uint_as_float(u & 0xffff0000u); }

__device__ __forceinline__ uint32_t enc(float f) { uint32_t u = ~__float_as_uint(f); return u ? u : 0x80000000u; }
__device__ __forceinline__ float dec(uint32_t u) { return __uint_as_float(~u); }
__device__ __forceinline__ void st_rlx2(uint32_t* p, uint32_t a, uint32_t b) { asm volatile("st.relaxed.gpu.global.v2.u32 [%0], {%1,%2};" ::"l"(p), "r"(a), "r"(b) : "memory"); }
__device__ __forceinline__ void st_rlx4(uint32_t* p, uint32_t a) { asm volatile("st.relaxed.gpu.global.v4.u32 [%0], {%1,%1,%1,%1};" ::"l"(p), "r"(a) : "memory"); }
__device__ __forceinline__ uint32_t ld_rlx(const uint32_t* p) { uint32_t v; asm volatile("ld.relaxed.gpu.global.u32 %0, [%1];" : "=r"(v) : "l"(p) : "memory"); return v; }
__device__ __forceinline__ uint4 ld_rlx4(const uint32_t* p) { uint4 v; asm volatile("ld.relaxed.gpu.global.v4.u32 {%0,%1,%2,%3}, [%4];" : "=r"(v.x), "=r"(v.y), "=r"(v.z), "=r"(v.w) : "l"(p) : "memory"); return v; }
__device__ __forceinline__ uint32_t min4(uint4 v) { return min(min(v.x, v.y), min(v.z, v.w)); }

constexpr float SCALE_LOG2E = 0.08838834764831845f * 1.4426950408889634f;

__global__ void __cluster_dims__(NSPLIT, 1, 1) __launch_bounds__(NTHREADS, 1) gqa_decode_fused(const __grid_constant__ Params P) {
    extern __shared__ __align__(1024) unsigned char smem[];
    const int tid = threadIdx.x;
    const int cta = blockIdx.x;
    const int group = cta >> 1, s = cta & 1;
    const int br = group >> 4, h = group & 15;
    {
        const __nv_bfloat16* w = P.wq[br] + (size_t)(s * QROWS_PER_CTA + (tid >> 2)) * QCOLS + h * 256 + (tid & 3) * 64;
#pragma unroll
        for (int i = 0; i < PFN; i++)
            if (tid < 256) asm volatile("prefetch.global.L2 [%0];" ::"l"(w + (size_t)i * 64 * QCOLS));
    }
    const int warp = __shfl_sync(0xffffffffu, tid >> 5, 0), lane = tid & 31;

    uint32_t sb;
    asm volatile("mov.u32 %0, %1;" : "=r"(sb) : "r"(smem_u32(smem)));
    const int g = lane >> 2, t = lane & 3;
    const uint32_t bar_full = sb + SM_BAR, bar_empty = bar_full + NS * 8, bar_wq = bar_empty + NS * 8;
    const uint32_t bar_pq = bar_wq + 8 * 8, bar_po = bar_pq + 8;
    float* red = reinterpret_cast<float*>(smem + SM_RED);
    volatile uint32_t* ctl = reinterpret_cast<volatile uint32_t*>(smem + SM_CTL);
    uint32_t* const rbox = P.mail;
    unsigned long long* const cword = reinterpret_cast<unsigned long long*>(P.mail + RBOX_WORDS);
    unsigned long long cold = 0;

    if (warp < 8) {
        const int grp = warp >> 2, w4 = warp & 3;
        const int row0 = s * QROWS_PER_CTA + grp * 36 + w4 * 9;
        const uint32_t wsm = sb + SM_RING + (WQ_SLOT0 + grp) * SLOT_BYTES + w4 * 9 * 512;
        const uint32_t wbar = bar_wq + grp * 8;
        const int xl = lane < 27 ? lane : 0;
        const float xv = __bfloat162float(P.x[br][row0 + 72 * (xl / 9) + xl % 9]);
        const float xw = __bfloat162float(P.x[br][row0 + 216 + (lane < 9 ? lane : 0)]);
        cluster_arrive();
        bar_sync(1, 288);
        float a[8];
#pragma unroll
        for (int j = 0; j < 8; j++) a[j] = 0.f;
#pragma unroll 1
        for (int j = 0; j < 4; j++) {
            mbar_wait(wbar + j * 16, 0);
            const float xs = j < 3 ? xv : xw;
            const int xb = j < 3 ? 9 * j : 0;
#pragma unroll
            for (int i = 0; i < 9; i++) {
                const uint4 w = lds128(wsm + j * 2 * SLOT_BYTES + i * 512 + lane * 16);
                const float xi = __shfl_sync(0xffffffffu, xs, xb + i);
                a[0] = fmaf(xi, bf_lo(w.x), a[0]); a[1] = fmaf(xi, bf_hi(w.x), a[1]);
                a[2] = fmaf(xi, bf_lo(w.y), a[2]); a[3] = fmaf(xi, bf_hi(w.y), a[3]);
                a[4] = fmaf(xi, bf_lo(w.z), a[4]); a[5] = fmaf(xi, bf_hi(w.z), a[5]);
                a[6] = fmaf(xi, bf_lo(w.w), a[6]); a[7] = fmaf(xi, bf_hi(w.w), a[7]);
            }
            __syncwarp();
            if (lane == 0) mbar_arrive(bar_empty + (WQ_SLOT0 + 2 * j + grp) * 8);
        }
        float4* dst = reinterpret_cast<float4*>(red + warp * 256 + lane * 8);
        dst[0] = make_float4(a[0], a[1], a[2], a[3]);
        dst[1] = make_float4(a[4], a[5], a[6], a[7]);
        cluster_wait();
        bar_sync(1, 256);
        uint32_t peer;
        asm volatile("mapa.shared::cluster.u32 %0, %1, %2;" : "=r"(peer) : "r"(sb), "r"(s ^ 1));
        {
            float part = 0.f;
#pragma unroll
            for (int w8 = 0; w8 < 8; w8++) part += red[w8 * 256 + tid];
            st_peer(peer + SM_PQ + tid * 4, part, peer + (bar_pq - sb));
            mbar_wait_cluster(bar_pq, 0);
            reinterpret_cast<__nv_bfloat16*>(smem + SM_Q)[tid] = __float2bfloat16(part + reinterpret_cast<const float*>(smem + SM_PQ)[tid]);
        }
        bar_sync(1, 256);

        uint4 qf[4];
#pragma unroll
        for (int j = 0; j < 4; j++)
            qf[j] = lds128(sb + SM_Q + (g & 1) * 256 + ((4 * (j ^ (g >> 2)) + t) << 4));

        const uint32_t koffA = (w4 * 16 + g) * 256 + t * 16 + (g & 1) * 64;
        const uint32_t koffB = (w4 * 16 + g) * 256 + t * 16 + ((g & 1) ^ 1) * 64;
        const int vi = lane & 7;
        const int vkey = 8 * (lane >> 4) + ((vi < 4) ? 2 * vi : 2 * (vi - 4) + 1);
        const uint32_t voff = (w4 * 16 + vkey) * 256 + ((((lane >> 3) & 1) ^ vi) << 4);
        const int kap = (g >> 1) | ((g & 1) << 2);
        const bool valid = (t >> 1) == (g & 1);
        const uint32_t amask = (t == (kap >> 1)) ? ((kap & 1) ? 0xffff0000u : 0x0000ffffu) : 0u;

        float acc[16][4];
#pragma unroll
        for (int i = 0; i < 16; i++) { acc[i][0] = acc[i][1] = acc[i][2] = acc[i][3] = 0.f; }
        float m0 = -INFINITY, m1 = -INFINITY, l0 = 0.f, l1 = 0.f;
        uint32_t fbar = bar_full + grp * 8, tbase = sb + SM_RING + grp * SLOT_BYTES, ph = 0;
        auto advance = [&]() {
            __syncwarp();
            if (lane == 0) mbar_arrive(fbar + NS * 8);
            fbar += 16; tbase += 2 * SLOT_BYTES;
            if (fbar >= bar_empty) { fbar -= NS * 8; tbase -= NS * SLOT_BYTES; ph ^= 1; }
        };
        auto sample = [&](int i) {
            if ((tid & 127) == 0 && i >= CTL_FIRST && i < CTL_STOP + 4) {
                int e = (int)(gtime32() - ctl[i & 15]) - LAT_TARGET;
                e = max(min(e, 2000), -1000);
                if (i < CTL_STOP)
                    asm volatile("red.relaxed.gpu.global.add.u64 [%0], %1;" ::"l"(cword), "l"((unsigned long long)(long long)e << 32) : "memory");
                else
                    asm volatile("atom.relaxed.gpu.global.add.u64 %0, [%1], %2;" : "=l"(cold) : "l"(cword), "l"(1ull) : "memory");
            }
        };
#pragma unroll 1
        for (int it = 0; it < NTILES / PH; it++) {
            float sv[PU][4];
#pragma unroll
            for (int u = 0; u < PU; u++) {
                mbar_wait(fbar, ph);
                if (u & 1) sample(2 * PH * it + 2 * u + grp);
                float sa[4] = {0.f, 0.f, 0.f, 0.f}, sc[4] = {0.f, 0.f, 0.f, 0.f};
                uint4 L[4], H[4];
                L[0] = lds128(tbase + koffA);       H[0] = lds128(tbase + koffA + 2048);
                L[1] = lds128(tbase + koffB);       H[1] = lds128(tbase + koffB + 2048);
                L[2] = lds128(tbase + koffA + 128); H[2] = lds128(tbase + koffA + 128 + 2048);
                L[3] = lds128(tbase + koffB + 128); H[3] = lds128(tbase + koffB + 128 + 2048);
#pragma unroll
                for (int j = 0; j < 4; j++) {
                    mma16816(sa, L[j].x, H[j].x, L[j].y, H[j].y, qf[j].x, qf[j].y);
                    mma16816(sc, L[j].z, H[j].z, L[j].w, H[j].w, qf[j].z, qf[j].w);
                }
                advance();
#pragma unroll
                for (int e = 0; e < 4; e++) sv[u][e] = valid ? sa[e] + sc[e] : -INFINITY;
            }
            float x0 = fmaxf(sv[0][0], sv[0][2]), x1 = fmaxf(sv[0][1], sv[0][3]);
#pragma unroll
            for (int u = 1; u < PU; u++) { x0 = fmaxf(x0, fmaxf(sv[u][0], sv[u][2])); x1 = fmaxf(x1, fmaxf(sv[u][1], sv[u][3])); }
#pragma unroll
            for (int o = 2; o <= 16; o <<= 1) {
                x0 = fmaxf(x0, __shfl_xor_sync(0xffffffffu, x0, o));
                x1 = fmaxf(x1, __shfl_xor_sync(0xffffffffu, x1, o));
            }
            if (x0 > m0 || x1 > m1) {
                const float n0 = fmaxf(m0, x0), n1 = fmaxf(m1, x1);
                const float a0 = ex2((m0 - n0) * SCALE_LOG2E), a1 = ex2((m1 - n1) * SCALE_LOG2E);
                m0 = n0; m1 = n1;
                l0 *= a0; l1 *= a1;
#pragma unroll
                for (int i = 0; i < 8; i++) {
                    acc[i][0] *= a0; acc[i][1] *= a0; acc[i][2] *= a0; acc[i][3] *= a0;
                    acc[8 + i][0] *= a1; acc[8 + i][1] *= a1; acc[8 + i][2] *= a1; acc[8 + i][3] *= a1;
                }
            }
            uint32_t pb[PU][4];
#pragma unroll
            for (int u = 0; u < PU; u++) {
                const float p0 = ex2((sv[u][0] - m0) * SCALE_LOG2E), p1 = ex2((sv[u][1] - m1) * SCALE_LOG2E);
                const float p2 = ex2((sv[u][2] - m0) * SCALE_LOG2E), p3 = ex2((sv[u][3] - m1) * SCALE_LOG2E);
                l0 += p0 + p2; l1 += p1 + p3;
                pb[u][0] = pack_bf16(p0, p0) & amask; pb[u][1] = pack_bf16(p1, p1) & amask;
                pb[u][2] = pack_bf16(p2, p2) & amask; pb[u][3] = pack_bf16(p3, p3) & amask;
            }
#pragma unroll
            for (int u = 0; u < PU; u++) {
                mbar_wait(fbar, ph);
                if (u & 1) sample(2 * PH * it + PH + 2 * u + grp);
#pragma unroll
                for (int j = 0; j < 8; j++) {
                    const uint4 a = ldsm4t(tbase + (voff ^ ((j & 3) << 5)) + (j >> 2) * 128);
                    mma16816(acc[j], a.x, a.y, a.z, a.w, pb[u][0], pb[u][2]);
                    mma16816(acc[8 + j], a.x, a.y, a.z, a.w, pb[u][1], pb[u][3]);
                }
                advance();
            }
        }

#pragma unroll
        for (int q = 0; q < 4; q++) {
            float r[8];
#pragma unroll
            for (int y = 0; y < 8; y++) r[y] = acc[4 * q + (y >> 1)][2 * (y & 1)] + acc[4 * q + ((y ^ 4) >> 1)][2 * (y & 1) + 1];
#pragma unroll
            for (int y = 0; y < 8; y += 2) r[y] += __shfl_xor_sync(0xffffffffu, r[y + 1], 1);
            r[0] += __shfl_xor_sync(0xffffffffu, r[2], 2);
            r[4] += __shfl_xor_sync(0xffffffffu, r[6], 2);
            float* dst2 = red + warp * 256 + q * 64 + t * 8 + g;
            dst2[0] = r[0];
            dst2[32] = r[4];
        }
#pragma unroll
        for (int o = 2; o <= 16; o <<= 1) {
            l0 += __shfl_xor_sync(0xffffffffu, l0, o);
            l1 += __shfl_xor_sync(0xffffffffu, l1, o);
        }
        float* ml = reinterpret_cast<float*>(smem + SM_ML);
        if (lane == 0) *reinterpret_cast<float4*>(ml + warp * 4) = make_float4(m0, l0, m1, l1);
        bar_sync(1, 256);
        {
            const int hd = tid >> 7;
            float2 w[8];
#pragma unroll
            for (int i = 0; i < 8; i++) w[i] = *reinterpret_cast<const float2*>(ml + i * 4 + hd * 2);
            float M = w[0].x;
#pragma unroll
            for (int i = 1; i < 8; i++) M = fmaxf(M, w[i].x);
            float o = 0.f, L = 0.f;
#pragma unroll
            for (int i = 0; i < 8; i++) {
                const float f = ex2((w[i].x - M) * SCALE_LOG2E);
                o = fmaf(f, red[i * 256 + tid], o);
                L = fmaf(f, w[i].y, L);
            }
            const int d = tid & 127;
            if (hd != s) {
                st_peer(peer + SM_PO + d * 4, o, peer + (bar_po - sb));
                if (d < 2) st_peer(peer + SM_PO + 512 + d * 4, d ? L : M, peer + (bar_po - sb));
            } else {
                mbar_wait_cluster(bar_po, 0);
                const float* pbuf = reinterpret_cast<const float*>(smem + SM_PO);
                const float Mp = pbuf[128], Lp = pbuf[129];
                const float Mx = fmaxf(M, Mp);
                const float f = ex2((M - Mx) * SCALE_LOG2E), fp = ex2((Mp - Mx) * SCALE_LOG2E);
                reinterpret_cast<__nv_bfloat16*>(smem + SM_O)[d] = __float2bfloat16(__fdividef(f * o + fp * pbuf[d], f * L + fp * Lp));
            }
        }
    } else if (warp == 8) {
        const uint32_t t_entry = gtime32();
        if (lane == 0) {
            asm volatile("prefetch.param.tensormap [%0];" ::"l"(__cvta_generic_to_grid_constant(&P.wq_map[br])) : "memory");
#pragma unroll
            for (int i = 0; i < 8; i++) mbar_init(bar_wq + i * 8, 1);
        }
        __syncwarp();
        uint64_t pol;
        asm volatile("createpolicy.fractional.L2::evict_first.b64 %0, 1.0;" : "=l"(pol));
#pragma unroll
        for (int c = 0; c < 4; c++)
            expect_and_copy_2d(sb + SM_RING + (WQ_SLOT0 + c) * SLOT_BYTES, &P.wq_map[br], h * 256, s * QROWS_PER_CTA + c * 36, bar_wq + c * 8, pol);
        if (lane == 0) {
#pragma unroll
            for (int i = 0; i < 2 * NS; i++) mbar_init(bar_full + i * 8, i >= NS ? 4 : 1);
            mbar_init(bar_pq, 1);
            mbar_init(bar_po, 1);
            asm volatile("fence.mbarrier_init.release.cluster;" ::: "memory");
            mbar_expect_tx(bar_pq, 256 * 4);
            mbar_expect_tx(bar_po, 130 * 4);
#pragma unroll
            for (int i = 0; i < WQ_SLOT0; i++) mbar_arrive_n(bar_empty + i * 8, 4);
            ctl[16] = 0; ctl[17] = 0;
        }
        __syncwarp();
        cluster_arrive();
        bar_arrive(1, 288);
        bar_arrive(3, 96);
#pragma unroll
        for (int c = 4; c < 8; c++)
            expect_and_copy_2d(sb + SM_RING + (WQ_SLOT0 + c) * SLOT_BYTES, &P.wq_map[br], h * 256, s * QROWS_PER_CTA + c * 36, bar_wq + c * 8, pol);
        const size_t off = (size_t)h * SK * DH + (size_t)s * 8 * TILE_KEYS * DH;
        const unsigned char* kp = reinterpret_cast<const unsigned char*>(P.k[br] + off);
        const unsigned char* vp = reinterpret_cast<const unsigned char*>(P.v[br] + off);
        const unsigned char* wop = reinterpret_cast<const unsigned char*>(P.wo[br] + (size_t)(h * 256 + s * 128) * D_MODEL);
        if (lane == 0) {
            asm volatile("cp.async.bulk.prefetch.L2.global [%0], 16;" ::"l"(kp));
            asm volatile("cp.async.bulk.prefetch.L2.global [%0], 16;" ::"l"(vp));
            asm volatile("cp.async.bulk.prefetch.L2.global [%0], 16;" ::"l"(wop));
            asm volatile("cp.async.bulk.prefetch.L2.global [%0], 16;" ::"l"(wop + WO_CHUNKS * WO_CHUNK_BYTES - 16));
        }
        __syncwarp();
        const int dt = P.dt, dtw = dt + (dt >> 3);
        uint32_t tnext = 2 * P.t0 + ((cta * dt) >> 6);
        uint32_t sbar = bar_full, sdst = sb + SM_RING, eph = 0;
#pragma unroll 1
        for (int i = 0; i < NKV + WO_CHUNKS; i++) {
            const bool isw = i >= NKV;
            const int j = (i / (2 * PH)) * PH + (i % PH);
            const unsigned char* src = isw ? wop + (i - NKV) * WO_CHUNK_BYTES
                                           : (((i / PH) & 1) ? vp : kp) + (((j >> 3) << 4) + (j & 7)) * TILE_BYTES;
            mbar_wait(sbar + NS * 8, eph);
            unsigned n = 0;
            uint32_t now;
            const uint32_t due = t_entry + (tnext >> 1);
#pragma unroll 1
            do { now = gtime32(); } while ((int)(now - due - ctl[16]) < 0 && ++n < SPIN_LIMIT);
            if (lane == 0) ctl[i & 15] = now;
            expect_and_copy(sdst, src, isw ? WO_CHUNK_BYTES : TILE_BYTES, sbar, pol);
            tnext += isw ? dtw : dt;
            sbar += 8; sdst += SLOT_BYTES;
            if (sbar == bar_empty) { sbar = bar_full; sdst = sb + SM_RING; eph ^= 1; }
            if (i == CTL_STOP && lane == 0) ctl[17] = 1;
        }
        cluster_wait();
    } else {
        cluster_arrive();
        bar_sync(3, 96);
        cluster_wait();
        {
            unsigned n = 0;
#pragma unroll 1
            while (ctl[17] == 0 && ++n < SPIN_LIMIT) {
                __nanosleep(CTL_NAP);
                if (warp == 9) {
                    const int sum = (int)ld_rlx(reinterpret_cast<const uint32_t*>(cword) + 1);
                    if (lane == 0) ctl[16] = (uint32_t)max(min(((sum >> 6) * CTL_GAIN) >> 8, 20000), -20000);
                }
            }
        }
        const int ridx = 2 * (cta & (NSRC - 1)) + (warp - 9);
        if (ridx < NRED) {
            uint32_t* rin = rbox + ((br * NRED + ridx) * NSRC + (lane >> 2)) * 16 + (lane & 3) * 4;
            uint32_t* outp = reinterpret_cast<uint32_t*>(P.out + br * D_MODEL + ridx * 16) + (lane & 7);
            const bool hi = lane & 4;
            uint4 r[4];
            unsigned n = 0;
            float a0, a1, a2, a3;
            auto take = [&](const uint4 (&v)[4]) {
                a0 = (dec(v[0].x) + dec(v[1].x)) + (dec(v[2].x) + dec(v[3].x));
                a1 = (dec(v[0].y) + dec(v[1].y)) + (dec(v[2].y) + dec(v[3].y));
                a2 = (dec(v[0].z) + dec(v[1].z)) + (dec(v[2].z) + dec(v[3].z));
                a3 = (dec(v[0].w) + dec(v[1].w)) + (dec(v[2].w) + dec(v[3].w));
                return __all_sync(0xffffffffu, min(min(min4(v[0]), min4(v[1])), min(min4(v[2]), min4(v[3]))) != 0);
            };
#pragma unroll 1
            do {
#pragma unroll
                for (int i = 0; i < 4; i++) r[i] = ld_rlx4(rin + i * 128);
            } while (!take(r) && ++n < SPIN_LIMIT);
            float lo = (hi ? a1 : a0) + __shfl_xor_sync(0xffffffffu, hi ? a0 : a1, 4);
            float up = (hi ? a3 : a2) + __shfl_xor_sync(0xffffffffu, hi ? a2 : a3, 4);
            lo += __shfl_xor_sync(0xffffffffu, lo, 8);  up += __shfl_xor_sync(0xffffffffu, up, 8);
            lo += __shfl_xor_sync(0xffffffffu, lo, 16); up += __shfl_xor_sync(0xffffffffu, up, 16);
            if (lane < 8) asm volatile("st.global.u32 [%0], %1;" ::"l"(outp), "r"(pack_bf16(lo, up)) : "memory");
#pragma unroll
            for (int i = 0; i < 4; i++) st_rlx4(rin + i * 128, 0u);
        }
        return;
    }

    {
        const int i8 = lane & 7;
        const uint32_t woff = sb + SM_RING + (8 * (lane >> 4) + i8) * WO_ROW_BYTES + warp * 128 + ((((lane >> 3) & 1) ^ i8) << 4);
        const uint32_t omask = (t == (g >> 1)) ? ((g & 1) ? 0xffff0000u : 0x0000ffffu) : 0u;
        uint32_t* rout = rbox + ((br * NRED + 4 * warp + t) * NSRC + (cta & (NSRC - 1))) * 16 + 2 * g;
        float c[4][4], c2[4][4];
#pragma unroll
        for (int i = 0; i < 4; i++) { c[i][0] = c[i][1] = c[i][2] = c[i][3] = 0.f; c2[i][0] = c2[i][1] = c2[i][2] = c2[i][3] = 0.f; }
        bar_sync(2, 288);
        const uint32_t* o32 = reinterpret_cast<const uint32_t*>(smem + SM_O);
        uint32_t ob[2 * WO_CHUNKS];
#pragma unroll
        for (int j = 0; j < 2 * WO_CHUNKS; j++) ob[j] = o32[4 * j + t] & omask;
#pragma unroll
        for (int ks = 0; ks < WO_CHUNKS - 2; ks += 2) {
            mbar_wait(bar_full + ((NKV + ks) % NS) * 8, ((NKV + ks) / NS) & 1);
            mbar_wait(bar_full + ((NKV + ks + 1) % NS) * 8, ((NKV + ks + 1) / NS) & 1);
            uint4 a[8];
#pragma unroll
            for (int j = 0; j < 8; j++) a[j] = ldsm4t((woff ^ ((j & 3) << 5)) + ((NKV + ks + (j >> 2)) % NS) * SLOT_BYTES);
#pragma unroll
            for (int j = 0; j < 4; j++) {
                mma16816(c[j], a[j].x, a[j].y, a[j].z, a[j].w, ob[2 * ks], ob[2 * ks + 1]);
                mma16816(c2[j], a[4 + j].x, a[4 + j].y, a[4 + j].z, a[4 + j].w, ob[2 * ks + 2], ob[2 * ks + 3]);
            }
        }
#pragma unroll
        for (int ks = WO_CHUNKS - 2; ks < WO_CHUNKS; ks++) {
            mbar_wait(bar_full + ((NKV + ks) % NS) * 8, ((NKV + ks) / NS) & 1);
#pragma unroll
            for (int j = 0; j < 4; j++) {
                const uint4 a = ldsm4t((woff ^ (j << 5)) + ((NKV + ks) % NS) * SLOT_BYTES);
                if (ks & 1) mma16816(c[j], a.x, a.y, a.z, a.w, ob[2 * ks], ob[2 * ks + 1]);
                else mma16816(c2[j], a.x, a.y, a.z, a.w, ob[2 * ks], ob[2 * ks + 1]);
            }
            if (ks == WO_CHUNKS - 2) {
#pragma unroll
                for (int j = 0; j < 4; j++) { c[j][0] += c2[j][0]; c[j][1] += c2[j][1]; c[j][2] += c2[j][2]; c[j][3] += c2[j][3]; }
            }
        }
        float r[8];
#pragma unroll
        for (int y = 0; y < 8; y++) r[y] = c[y >> 1][2 * (y & 1)] + c[y >> 1][2 * ((y ^ 1) & 1) + 1];
        r[0] += __shfl_xor_sync(0xffffffffu, r[2], 1);
        r[1] += __shfl_xor_sync(0xffffffffu, r[3], 1);
        r[4] += __shfl_xor_sync(0xffffffffu, r[6], 1);
        r[5] += __shfl_xor_sync(0xffffffffu, r[7], 1);
        r[0] += __shfl_xor_sync(0xffffffffu, r[4], 2);
        r[1] += __shfl_xor_sync(0xffffffffu, r[5], 2);
        st_rlx2(rout, enc(r[0]), enc(r[1]));
        if ((uint32_t)cold == 2 * NCTA - 1)
            asm volatile("st.relaxed.gpu.global.u64 [%0], %1;" ::"l"(cword), "l"(0ull) : "memory");
    }
}

}

extern "C" void kernel_launch(void* const* d_in, const int* in_sizes, int n_in, void* d_out, int out_size) {
    (void)in_sizes; (void)n_in; (void)out_size;
    typedef CUresult (*EncodeFn)(CUtensorMap*, CUtensorMapDataType, cuuint32_t, void*, const cuuint64_t*, const cuuint64_t*,
                                 const cuuint32_t*, const cuuint32_t*, CUtensorMapInterleave, CUtensorMapSwizzle,
                                 CUtensorMapL2promotion, CUtensorMapFloatOOBfill);
    static EncodeFn encode = nullptr;
    static uint32_t* mail = nullptr;
    static int dt = 655;
    if (!mail) {
        cudaFuncSetAttribute(gqa_decode_fused, cudaFuncAttributeMaxDynamicSharedMemorySize, SM_TOTAL);
        void* p = nullptr;
        cudaGetSymbolAddress(&p, g_mail);
        mail = (uint32_t*)p;
        cudaDriverEntryPointQueryResult qres;
        cudaGetDriverEntryPoint("cuTensorMapEncodeTiled", &p, cudaEnableDefault, &qres);
        encode = (EncodeFn)p;
        int dev = 0, khz = 0, bits = 0;
        cudaGetDevice(&dev);
        if (cudaDeviceGetAttribute(&khz, cudaDevAttrMemoryClockRate, dev) == cudaSuccess &&
            cudaDeviceGetAttribute(&bits, cudaDevAttrGlobalMemoryBusWidth, dev) == cudaSuccess && khz > 0 && bits > 0) {
            const double bytes_per_ns = 2.0 * khz * 1e-6 * bits / 8.0;
            dt = (int)(2.0 * NCTA * TILE_BYTES / (0.955 * bytes_per_ns) + 0.5);
        }
        (void)cudaGetLastError();
    }
    Params p;
    for (int b = 0; b < 2; b++) {
        p.x[b] = (const __nv_bfloat16*)d_in[5 * b + 0];
        p.k[b] = (const __nv_bfloat16*)d_in[5 * b + 1];
        p.v[b] = (const __nv_bfloat16*)d_in[5 * b + 2];
        p.wq[b] = (const __nv_bfloat16*)d_in[5 * b + 3];
        p.wo[b] = (const __nv_bfloat16*)d_in[5 * b + 4];
        const cuuint64_t dims[2] = {(cuuint64_t)QCOLS, (cuuint64_t)D_MODEL};
        const cuuint64_t strides[1] = {(cuuint64_t)QCOLS * 2};
        const cuuint32_t box[2] = {256, 36}, estr[2] = {1, 1};
        encode(&p.wq_map[b], CU_TENSOR_MAP_DATA_TYPE_BFLOAT16, 2, d_in[5 * b + 3], dims, strides, box, estr,
               CU_TENSOR_MAP_INTERLEAVE_NONE, CU_TENSOR_MAP_SWIZZLE_NONE, CU_TENSOR_MAP_L2_PROMOTION_NONE,
               CU_TENSOR_MAP_FLOAT_OOB_FILL_NONE);
    }
    p.out = (__nv_bfloat16*)d_out;
    p.mail = mail;
    p.dt = dt;
    p.t0 = dt * 9 / 2 - T0_LEAD;
    gqa_decode_fused<<<NCTA, NTHREADS, SM_TOTAL>>>(p);
}
```

```cpp
#include <cuda.h>
#include <cuda_runtime.h>
#include <cuda_bf16.h>
#include <stdint.h>

namespace {

constexpr int D_MODEL = 576;
constexpr int HKV = 16;
constexpr int SK = 8192;
constexpr int DH = 128;
constexpr int QCOLS = 4096;
constexpr int NSPLIT = 2;
constexpr int NCTA = 2 * HKV * NSPLIT;
constexpr int TILE_KEYS = 64;
constexpr int TILE_BYTES = TILE_KEYS * DH * 2;
constexpr int NTILES = SK / NSPLIT / TILE_KEYS;
constexpr int NKV = 2 * NTILES;
constexpr int PH = 4;
constexpr int PU = PH / 2;
static_assert(PH == 4 && NKV == 128, "the producer's tile order is written for this shape");
constexpr int NS = 12;
constexpr int WO_ROW_BYTES = D_MODEL * 2;
constexpr int WO_CHUNK_BYTES = 16 * WO_ROW_BYTES;
constexpr int WO_CHUNKS = 8;
constexpr int SLOT_BYTES = WO_CHUNK_BYTES;
constexpr int WQ_SLOT0 = NS - 8;
constexpr int QROWS_PER_CTA = D_MODEL / NSPLIT;
constexpr int NTHREADS = 352;
constexpr int NRED = 36;
constexpr int NSRC = HKV * NSPLIT;
constexpr unsigned SPIN_LIMIT = 1u << 19;

#define LAT_TARGET 1750
#define CTL_GAIN 22
#define PFN 3
#define T0_LEAD 900
constexpr int CTL_FIRST = 12, CTL_STOP = NKV - 8, CTL_NAP = 500;

constexpr int SM_RING = 0;
constexpr int SM_RED = SM_RING + NS * SLOT_BYTES;
constexpr int SM_PQ = SM_RED + 8 * 256 * 4;
constexpr int SM_PO = SM_PQ + 1024;
constexpr int SM_ML = SM_PO + 528;
constexpr int SM_Q = SM_ML + 128;
constexpr int SM_O = SM_Q;
constexpr int SM_BAR = SM_Q + 512;
constexpr int SM_CTL = SM_BAR + (2 * NS + 10) * 8;
constexpr int SM_TOTAL = SM_CTL + 80;
static_assert(SM_TOTAL <= 232448, "shared memory");

constexpr int RBOX_WORDS = 2 * NRED * NSRC * 16;
__device__ __align__(1024) uint32_t g_mail[RBOX_WORDS + 32];

struct Params {
    const __nv_bfloat16* wq[2];
    const __nv_bfloat16* x[2];
    const __nv_bfloat16* k[2];
    const __nv_bfloat16* v[2];
    const __nv_bfloat16* wo[2];
    __nv_bfloat16* out;
    uint32_t* mail;
    int dt, t0;
    CUtensorMap wq_map[2];
};

__device__ __forceinline__ uint32_t gtime32() { uint32_t t; asm volatile("mov.u32 %0, %globaltimer_lo;" : "=r"(t)); return t; }
__device__ __forceinline__ uint32_t smem_u32(const void* p) { return (uint32_t)__cvta_generic_to_shared(p); }
__device__ __forceinline__ void mbar_init(uint32_t bar, uint32_t cnt) {
    asm volatile("mbarrier.init.shared::cta.b64 [%0], %1;" ::"r"(bar), "r"(cnt) : "memory");
}
__device__ __forceinline__ void mbar_expect_tx(uint32_t bar, uint32_t bytes) {
    asm volatile("mbarrier.arrive.expect_tx.shared::cta.b64 _, [%0], %1;" ::"r"(bar), "r"(bytes) : "memory");
}
__device__ __forceinline__ void mbar_arrive(uint32_t bar) {
    asm volatile("mbarrier.arrive.shared::cta.b64 _, [%0];" ::"r"(bar) : "memory");
}
__device__ __forceinline__ void mbar_arrive_n(uint32_t bar, uint32_t n) {
    asm volatile("mbarrier.arrive.shared::cta.b64 _, [%0], %1;" ::"r"(bar), "r"(n) : "memory");
}
__device__ __forceinline__ void mbar_wait(uint32_t bar, uint32_t parity) {
    unsigned n = 0;
    uint32_t ok;
#pragma unroll 1
    do {
        asm volatile("{\n.reg .pred p;\nmbarrier.try_wait.parity.shared::cta.b64 p, [%1], %2;\nselp.u32 %0, 1, 0, p;\n}"
                     : "=r"(ok) : "r"(bar), "r"(parity) : "memory");
    } while (!ok && ++n <= SPIN_LIMIT);
}
__device__ __forceinline__ void mbar_wait_cluster(uint32_t bar, uint32_t parity) {
    unsigned n = 0;
    uint32_t ok;
#pragma unroll 1
    do {
        asm volatile("{\n.reg .pred p;\nmbarrier.try_wait.parity.acquire.cluster.shared::cta.b64 p, [%1], %2;\nselp.u32 %0, 1, 0, p;\n}"
                     : "=r"(ok) : "r"(bar), "r"(parity) : "memory");
    } while (!ok && ++n <= SPIN_LIMIT);
}
__device__ __forceinline__ void expect_and_copy(uint32_t dst, const void* src, uint32_t bytes, uint32_t bar, uint64_t pol) {
    asm volatile("{\n.reg .pred p;\nelect.sync _|p, 0xffffffff;\n"
                 "@p mbarrier.arrive.expect_tx.shared::cta.b64 _, [%3], %2;\n"
                 "@p cp.async.bulk.shared::cluster.global.mbarrier::complete_tx::bytes.L2::cache_hint [%0], [%1], %2, [%3], %4;\n}"
                 ::"r"(dst), "l"(src), "r"(bytes), "r"(bar), "l"(pol) : "memory");
}
__device__ __forceinline__ void expect_and_copy_2d(uint32_t dst, const CUtensorMap* map, int c0, int c1, uint32_t bar, uint64_t pol) {
    asm volatile("{\n.reg .pred p;\nelect.sync _|p, 0xffffffff;\n"
                 "@p mbarrier.arrive.expect_tx.shared::cta.b64 _, [%2], %6;\n"
                 "@p cp.async.bulk.tensor.2d.shared::cluster.global.mbarrier::complete_tx::bytes.L2::cache_hint [%0], [%1, {%3, %4}], [%2], %5;\n}"
                 ::"r"(dst), "l"(map), "r"(bar), "r"(c0), "r"(c1), "l"(pol), "n"(SLOT_BYTES) : "memory");
}
__device__ __forceinline__ void st_peer(uint32_t peer_addr, float v, uint32_t peer_bar) {
    asm volatile("st.async.shared::cluster.mbarrier::complete_tx::bytes.f32 [%0], %1, [%2];" ::"r"(peer_addr), "f"(v), "r"(peer_bar) : "memory");
}
__device__ __forceinline__ void bar_sync(int id, int n) { asm volatile("bar.sync %0, %1;" ::"r"(id), "r"(n) : "memory"); }
__device__ __forceinline__ void bar_arrive(int id, int n) { asm volatile("bar.arrive %0, %1;" ::"r"(id), "r"(n) : "memory"); }
__device__ __forceinline__ void cluster_arrive() { asm volatile("barrier.cluster.arrive.relaxed.aligned;" ::: "memory"); }
__device__ __forceinline__ void cluster_wait() { asm volatile("barrier.cluster.wait.acquire.aligned;" ::: "memory"); }

__device__ __forceinline__ uint4 lds128(uint32_t a) {
    uint4 v;
    asm volatile("ld.shared.v4.u32 {%0,%1,%2,%3}, [%4];" : "=r"(v.x), "=r"(v.y), "=r"(v.z), "=r"(v.w) : "r"(a) : "memory");
    return v;
}
__device__ __forceinline__ uint4 ldsm4t(uint32_t a) {
    uint4 v;
    asm volatile("ldmatrix.sync.aligned.m8n8.x4.trans.shared.b16 {%0,%1,%2,%3}, [%4];"
                 : "=r"(v.x), "=r"(v.y), "=r"(v.z), "=r"(v.w) : "r"(a) : "memory");
    return v;
}
__device__ __forceinline__ void mma16816(float (&c)[4], uint32_t a0, uint32_t a1, uint32_t a2, uint32_t a3, uint32_t b0, uint32_t b1) {
    asm volatile("mma.sync.aligned.m16n8k16.row.col.f32.bf16.bf16.f32 {%0,%1,%2,%3}, {%4,%5,%6,%7}, {%8,%9}, {%0,%1,%2,%3};"
                 : "+f"(c[0]), "+f"(c[1]), "+f"(c[2]), "+f"(c[3])
                 : "r"(a0), "r"(a1), "r"(a2), "r"(a3), "r"(b0), "r"(b1));
}
__device__ __forceinline__ uint32_t pack_bf16(float lo, float hi) {
    uint32_t r;
    asm("cvt.rn.bf16x2.f32 %0, %1, %2;" : "=r"(r) : "f"(hi), "f"(lo));
    return r;
}
__device__ __forceinline__ float ex2(float x) { float y; asm("ex2.approx.ftz.f32 %0, %1;" : "=f"(y) : "f"(x)); return y; }
__device__ __forceinline__ float bf_lo(uint32_t u) { return __uint_as_float(u << 16); }
__device__ __forceinline__ float bf_hi(uint32_t u) { return __uint_as_float(u & 0xffff0000u); }

__device__ __forceinline__ uint32_t enc(float f) { uint32_t u = ~__float_as_uint(f); return u ? u : 0x80000000u; }
__device__ __forceinline__ float dec(uint32_t u) { return __uint_as_float(~u); }
__device__ __forceinline__ void st_rlx2(uint32_t* p, uint32_t a, uint32_t b) { asm volatile("st.relaxed.gpu.global.v2.u32 [%0], {%1,%2};" ::"l"(p), "r"(a), "r"(b) : "memory"); }
__device__ __forceinline__ void st_rlx4(uint32_t* p, uint32_t a) { asm volatile("st.relaxed.gpu.global.v4.u32 [%0], {%1,%1,%1,%1};" ::"l"(p), "r"(a) : "memory"); }
__device__ __forceinline__ uint32_t ld_rlx(const uint32_t* p) { uint32_t v; asm volatile("ld.relaxed.gpu.global.u32 %0, [%1];" : "=r"(v) : "l"(p) : "memory"); return v; }
__device__ __forceinline__ uint4 ld_rlx4(const uint32_t* p) { uint4 v; asm volatile("ld.relaxed.gpu.global.v4.u32 {%0,%1,%2,%3}, [%4];" : "=r"(v.x), "=r"(v.y), "=r"(v.z), "=r"(v.w) : "l"(p) : "memory"); return v; }
__device__ __forceinline__ uint32_t min4(uint4 v) { return min(min(v.x, v.y), min(v.z, v.w)); }

constexpr float SCALE_LOG2E = 0.08838834764831845f * 1.4426950408889634f;

__global__ void __cluster_dims__(NSPLIT, 1, 1) __launch_bounds__(NTHREADS, 1) gqa_decode_fused(const __grid_constant__ Params P) {
    extern __shared__ __align__(1024) unsigned char smem[];
    const int tid = threadIdx.x;
    const int cta = blockIdx.x;
    const int group = cta >> 1, s = cta & 1;
    const int br = group >> 4, h = group & 15;
    {
        const __nv_bfloat16* w = P.wq[br] + (size_t)(s * QROWS_PER_CTA + (tid >> 2)) * QCOLS + h * 256 + (tid & 3) * 64;
#pragma unroll
        for (int i = 0; i < PFN; i++)
            if (tid < 256) asm volatile("prefetch.global.L2 [%0];" ::"l"(w + (size_t)i * 64 * QCOLS));
    }
    const int warp = __shfl_sync(0xffffffffu, tid >> 5, 0), lane = tid & 31;

    uint32_t sb;
    asm volatile("mov.u32 %0, %1;" : "=r"(sb) : "r"(smem_u32(smem)));
    const int g = lane >> 2, t = lane & 3;
    const uint32_t bar_full = sb + SM_BAR, bar_empty = bar_full + NS * 8, bar_wq = bar_empty + NS * 8;
    const uint32_t bar_pq = bar_wq + 8 * 8, bar_po = bar_pq + 8;
    float* red = reinterpret_cast<float*>(smem + SM_RED);
    volatile uint32_t* ctl = reinterpret_cast<volatile uint32_t*>(smem + SM_CTL);
    uint32_t* const rbox = P.mail;
    unsigned long long* const cword = reinterpret_cast<unsigned long long*>(P.mail + RBOX_WORDS);
    unsigned long long cold = 0;

    if (warp < 8) {
        const int grp = warp >> 2, w4 = warp & 3;
        const int row0 = s * QROWS_PER_CTA + grp * 36 + w4 * 9;
        const uint32_t wsm = sb + SM_RING + (WQ_SLOT0 + grp) * SLOT_BYTES + w4 * 9 * 512;
        const uint32_t wbar = bar_wq + grp * 8;
        const int xl = lane < 27 ? lane : 0;
        const float xv = __bfloat162float(P.x[br][row0 + 72 * (xl / 9) + xl % 9]);
        const float xw = __bfloat162float(P.x[br][row0 + 216 + (lane < 9 ? lane : 0)]);
        cluster_arrive();
        bar_sync(1, 288);
        float a[8];
#pragma unroll
        for (int j = 0; j < 8; j++) a[j] = 0.f;
#pragma unroll 1
        for (int j = 0; j < 4; j++) {
            mbar_wait(wbar + j * 16, 0);
            const float xs = j < 3 ? xv : xw;
            const int xb = j < 3 ? 9 * j : 0;
#pragma unroll
            for (int i = 0; i < 9; i++) {
                const uint4 w = lds128(wsm + j * 2 * SLOT_BYTES + i * 512 + lane * 16);
                const float xi = __shfl_sync(0xffffffffu, xs, xb + i);
                a[0] = fmaf(xi, bf_lo(w.x), a[0]); a[1] = fmaf(xi, bf_hi(w.x), a[1]);
                a[2] = fmaf(xi, bf_lo(w.y), a[2]); a[3] = fmaf(xi, bf_hi(w.y), a[3]);
                a[4] = fmaf(xi, bf_lo(w.z), a[4]); a[5] = fmaf(xi, bf_hi(w.z), a[5]);
                a[6] = fmaf(xi, bf_lo(w.w), a[6]); a[7] = fmaf(xi, bf_hi(w.w), a[7]);
            }
            __syncwarp();
            if (lane == 0) mbar_arrive(bar_empty + (WQ_SLOT0 + 2 * j + grp) * 8);
        }
        float4* dst = reinterpret_cast<float4*>(red + warp * 256 + lane * 8);
        dst[0] = make_float4(a[0], a[1], a[2], a[3]);
        dst[1] = make_float4(a[4], a[5], a[6], a[7]);
        cluster_wait();
        bar_sync(1, 256);
        uint32_t peer;
        asm volatile("mapa.shared::cluster.u32 %0, %1, %2;" : "=r"(peer) : "r"(sb), "r"(s ^ 1));
        {
            float part = 0.f;
#pragma unroll
            for (int w8 = 0; w8 < 8; w8++) part += red[w8 * 256 + tid];
            st_peer(peer + SM_PQ + tid * 4, part, peer + (bar_pq - sb));
            mbar_wait_cluster(bar_pq, 0);
            reinterpret_cast<__nv_bfloat16*>(smem + SM_Q)[tid] = __float2bfloat16(part + reinterpret_cast<const float*>(smem + SM_PQ)[tid]);
        }
        bar_sync(1, 256);

        uint4 qf[4];
#pragma unroll
        for (int j = 0; j < 4; j++)
            qf[j] = lds128(sb + SM_Q + (g & 1) * 256 + ((4 * (j ^ (g >> 2)) + t) << 4));

        const uint32_t koffA = (w4 * 16 + g) * 256 + t * 16 + (g & 1) * 64;
        const uint32_t koffB = (w4 * 16 + g) * 256 + t * 16 + ((g & 1) ^ 1) * 64;
        const int vi = lane & 7;
        const int vkey = 8 * (lane >> 4) + ((vi < 4) ? 2 * vi : 2 * (vi - 4) + 1);
        const uint32_t voff = (w4 * 16 + vkey) * 256 + ((((lane >> 3) & 1) ^ vi) << 4);
        const int kap = (g >> 1) | ((g & 1) << 2);
        const bool valid = (t >> 1) == (g & 1);
        const uint32_t amask = (t == (kap >> 1)) ? ((kap & 1) ? 0xffff0000u : 0x0000ffffu) : 0u;

        float acc[16][4];
#pragma unroll
        for (int i = 0; i < 16; i++) { acc[i][0] = acc[i][1] = acc[i][2] = acc[i][3] = 0.f; }
        float m0 = -INFINITY, m1 = -INFINITY, l0 = 0.f, l1 = 0.f;
        uint32_t fbar = bar_full + grp * 8, tbase = sb + SM_RING + grp * SLOT_BYTES, ph = 0;
        auto advance = [&]() {
            __syncwarp();
            if (lane == 0) mbar_arrive(fbar + NS * 8);
            fbar += 16; tbase += 2 * SLOT_BYTES;
            if (fbar >= bar_empty) { fbar -= NS * 8; tbase -= NS * SLOT_BYTES; ph ^= 1; }
        };
        auto sample = [&](int i) {
            if ((tid & 127) == 0 && i >= CTL_FIRST && i < CTL_STOP + 4) {
                int e = (int)(gtime32() - ctl[i & 15]) - LAT_TARGET;
                e = max(min(e, 2000), -1000);
                if (i < CTL_STOP)
                    asm volatile("red.relaxed.gpu.global.add.u64 [%0], %1;" ::"l"(cword), "l"((unsigned long long)(long long)e << 32) : "memory");
                else
                    asm volatile("atom.relaxed.gpu.global.add.u64 %0, [%1], %2;" : "=l"(cold) : "l"(cword), "l"(1ull) : "memory");
            }
        };
#pragma unroll 1
        for (int it = 0; it < NTILES / PH; it++) {
            float sv[PU][4];
#pragma unroll
            for (int u = 0; u < PU; u++) {
                mbar_wait(fbar, ph);
                if (u & 1) sample(2 * PH * it + 2 * u + grp);
                float sa[4] = {0.f, 0.f, 0.f, 0.f}, sc[4] = {0.f, 0.f, 0.f, 0.f};
                uint4 L[4], H[4];
                L[0] = lds128(tbase + koffA);       H[0] = lds128(tbase + koffA + 2048);
                L[1] = lds128(tbase + koffB);       H[1] = lds128(tbase + koffB + 2048);
                L[2] = lds128(tbase + koffA + 128); H[2] = lds128(tbase + koffA + 128 + 2048);
                L[3] = lds128(tbase + koffB + 128); H[3] = lds128(tbase + koffB + 128 + 2048);
#pragma unroll
                for (int j = 0; j < 4; j++) {
                    mma16816(sa, L[j].x, H[j].x, L[j].y, H[j].y, qf[j].x, qf[j].y);
                    mma16816(sc, L[j].z, H[j].z, L[j].w, H[j].w, qf[j].z, qf[j].w);
                }
                advance();
#pragma unroll
                for (int e = 0; e < 4; e++) sv[u][e] = valid ? sa[e] + sc[e] : -INFINITY;
            }
            float x0 = fmaxf(sv[0][0], sv[0][2]), x1 = fmaxf(sv[0][1], sv[0][3]);
#pragma unroll
            for (int u = 1; u < PU; u++) { x0 = fmaxf(x0, fmaxf(sv[u][0], sv[u][2])); x1 = fmaxf(x1, fmaxf(sv[u][1], sv[u][3])); }
#pragma unroll
            for (int o = 2; o <= 16; o <<= 1) {
                x0 = fmaxf(x0, __shfl_xor_sync(0xffffffffu, x0, o));
                x1 = fmaxf(x1, __shfl_xor_sync(0xffffffffu, x1, o));
            }
            if (x0 > m0 || x1 > m1) {
                const float n0 = fmaxf(m0, x0), n1 = fmaxf(m1, x1);
                const float a0 = ex2((m0 - n0) * SCALE_LOG2E), a1 = ex2((m1 - n1) * SCALE_LOG2E);
                m0 = n0; m1 = n1;
                l0 *= a0; l1 *= a1;
#pragma unroll
                for (int i = 0; i < 8; i++) {
                    acc[i][0] *= a0; acc[i][1] *= a0; acc[i][2] *= a0; acc[i][3] *= a0;
                    acc[8 + i][0] *= a1; acc[8 + i][1] *= a1; acc[8 + i][2] *= a1; acc[8 + i][3] *= a1;
                }
            }
            uint32_t pb[PU][4];
#pragma unroll
            for (int u = 0; u < PU; u++) {
                const float p0 = ex2((sv[u][0] - m0) * SCALE_LOG2E), p1 = ex2((sv[u][1] - m1) * SCALE_LOG2E);
                const float p2 = ex2((sv[u][2] - m0) * SCALE_LOG2E), p3 = ex2((sv[u][3] - m1) * SCALE_LOG2E);
                l0 += p0 + p2; l1 += p1 + p3;
                pb[u][0] = pack_bf16(p0, p0) & amask; pb[u][1] = pack_bf16(p1, p1) & amask;
                pb[u][2] = pack_bf16(p2, p2) & amask; pb[u][3] = pack_bf16(p3, p3) & amask;
            }
#pragma unroll
            for (int u = 0; u < PU; u++) {
                mbar_wait(fbar, ph);
                if (u & 1) sample(2 * PH * it + PH + 2 * u + grp);
#pragma unroll
                for (int j = 0; j < 8; j++) {
                    const uint4 a = ldsm4t(tbase + (voff ^ ((j & 3) << 5)) + (j >> 2) * 128);
                    mma16816(acc[j], a.x, a.y, a.z, a.w, pb[u][0], pb[u][2]);
                    mma16816(acc[8 + j], a.x, a.y, a.z, a.w, pb[u][1], pb[u][3]);
                }
                advance();
            }
        }

#pragma unroll
        for (int q = 0; q < 4; q++) {
            float r[8];
#pragma unroll
            for (int y = 0; y < 8; y++) r[y] = acc[4 * q + (y >> 1)][2 * (y & 1)] + acc[4 * q + ((y ^ 4) >> 1)][2 * (y & 1) + 1];
#pragma unroll
            for (int y = 0; y < 8; y += 2) r[y] += __shfl_xor_sync(0xffffffffu, r[y + 1], 1);
            r[0] += __shfl_xor_sync(0xffffffffu, r[2], 2);
            r[4] += __shfl_xor_sync(0xffffffffu, r[6], 2);
            float* dst2 = red + warp * 256 + q * 64 + t * 8 + g;
            dst2[0] = r[0];
            dst2[32] = r[4];
        }
#pragma unroll
        for (int o = 2; o <= 16; o <<= 1) {
            l0 += __shfl_xor_sync(0xffffffffu, l0, o);
            l1 += __shfl_xor_sync(0xffffffffu, l1, o);
        }
        float* ml = reinterpret_cast<float*>(smem + SM_ML);
        if (lane == 0) *reinterpret_cast<float4*>(ml + warp * 4) = make_float4(m0, l0, m1, l1);
        bar_sync(1, 256);
        {
            const int hd = tid >> 7;
            float2 w[8];
#pragma unroll
            for (int i = 0; i < 8; i++) w[i] = *reinterpret_cast<const float2*>(ml + i * 4 + hd * 2);
            float M = w[0].x;
#pragma unroll
            for (int i = 1; i < 8; i++) M = fmaxf(M, w[i].x);
            float o = 0.f, L = 0.f;
#pragma unroll
            for (int i = 0; i < 8; i++) {
                const float f = ex2((w[i].x - M) * SCALE_LOG2E);
                o = fmaf(f, red[i * 256 + tid], o);
                L = fmaf(f, w[i].y, L);
            }
            const int d = tid & 127;
            if (hd != s) {
                st_peer(peer + SM_PO + d * 4, o, peer + (bar_po - sb));
                if (d < 2) st_peer(peer + SM_PO + 512 + d * 4, d ? L : M, peer + (bar_po - sb));
            } else {
                mbar_wait_cluster(bar_po, 0);
                const float* pbuf = reinterpret_cast<const float*>(smem + SM_PO);
                const float Mp = pbuf[128], Lp = pbuf[129];
                const float Mx = fmaxf(M, Mp);
                const float f = ex2((M - Mx) * SCALE_LOG2E), fp = ex2((Mp - Mx) * SCALE_LOG2E);
                reinterpret_cast<__nv_bfloat16*>(smem + SM_O)[d] = __float2bfloat16(__fdividef(f * o + fp * pbuf[d], f * L + fp * Lp));
            }
        }
    } else if (warp == 8) {
        const uint32_t t_entry = gtime32();
        if (lane == 0) {
            asm volatile("prefetch.param.tensormap [%0];" ::"l"(__cvta_generic_to_grid_constant(&P.wq_map[br])) : "memory");
#pragma unroll
            for (int i = 0; i < 8; i++) mbar_init(bar_wq + i * 8, 1);
        }
        __syncwarp();
        uint64_t pol;
        asm volatile("createpolicy.fractional.L2::evict_first.b64 %0, 1.0;" : "=l"(pol));
#pragma unroll
        for (int c = 0; c < 4; c++)
            expect_and_copy_2d(sb + SM_RING + (WQ_SLOT0 + c) * SLOT_BYTES, &P.wq_map[br], h * 256, s * QROWS_PER_CTA + c * 36, bar_wq + c * 8, pol);
        if (lane == 0) {
#pragma unroll
            for (int i = 0; i < 2 * NS; i++) mbar_init(bar_full + i * 8, i >= NS ? 4 : 1);
            mbar_init(bar_pq, 1);
            mbar_init(bar_po, 1);
            asm volatile("fence.mbarrier_init.release.cluster;" ::: "memory");
            mbar_expect_tx(bar_pq, 256 * 4);
            mbar_expect_tx(bar_po, 130 * 4);
#pragma unroll
            for (int i = 0; i < WQ_SLOT0; i++) mbar_arrive_n(bar_empty + i * 8, 4);
            ctl[16] = 0; ctl[17] = 0;
        }
        __syncwarp();
        cluster_arrive();
        bar_arrive(1, 288);
        bar_arrive(3, 96);
#pragma unroll
        for (int c = 4; c < 8; c++)
            expect_and_copy_2d(sb + SM_RING + (WQ_SLOT0 + c) * SLOT_BYTES, &P.wq_map[br], h * 256, s * QROWS_PER_CTA + c * 36, bar_wq + c * 8, pol);
        const size_t off = (size_t)h * SK * DH + (size_t)s * 8 * TILE_KEYS * DH;
        const unsigned char* kp = reinterpret_cast<const unsigned char*>(P.k[br] + off);
        const unsigned char* vp = reinterpret_cast<const unsigned char*>(P.v[br] + off);
        const unsigned char* wop = reinterpret_cast<const unsigned char*>(P.wo[br] + (size_t)(h * 256 + s * 128) * D_MODEL);
        if (lane == 0) {
            asm volatile("cp.async.bulk.prefetch.L2.global [%0], 16;" ::"l"(kp));
            asm volatile("cp.async.bulk.prefetch.L2.global [%0], 16;" ::"l"(vp));
            asm volatile("cp.async.bulk.prefetch.L2.global [%0], 16;" ::"l"(wop));
            asm volatile("cp.async.bulk.prefetch.L2.global [%0], 16;" ::"l"(wop + WO_CHUNKS * WO_CHUNK_BYTES - 16));
        }
        __syncwarp();
        const int dt = P.dt, dtw = dt + (dt >> 3);
        uint32_t tnext = 2 * P.t0 + ((cta * dt) >> 6);
        uint32_t sbar = bar_full, sdst = sb + SM_RING, eph = 0;
#pragma unroll 1
        for (int i = 0; i < NKV + WO_CHUNKS; i++) {
            const bool isw = i >= NKV;
            const int tile = ((i >> 3) & 7) * 16 + (i >> 6) * 4 + (i & 3);
            const unsigned char* src = isw ? wop + (i - NKV) * WO_CHUNK_BYTES : ((i & 4) ? vp : kp) + tile * TILE_BYTES;
            mbar_wait(sbar + NS * 8, eph);
            unsigned n = 0;
            uint32_t now;
            const uint32_t due = t_entry + (tnext >> 1);
#pragma unroll 1
            do { now = gtime32(); } while ((int)(now - due - ctl[16]) < 0 && ++n < SPIN_LIMIT);
            if (lane == 0) ctl[i & 15] = now;
            expect_and_copy(sdst, src, isw ? WO_CHUNK_BYTES : TILE_BYTES, sbar, pol);
            tnext += isw ? dtw : dt;
            sbar += 8; sdst += SLOT_BYTES;
            if (sbar == bar_empty) { sbar = bar_full; sdst = sb + SM_RING; eph ^= 1; }
            if (i == CTL_STOP && lane == 0) ctl[17] = 1;
        }
        cluster_wait();
    } else {
        cluster_arrive();
        bar_sync(3, 96);
        cluster_wait();
        {
            unsigned n = 0;
#pragma unroll 1
            while (ctl[17] == 0 && ++n < SPIN_LIMIT) {
                __nanosleep(CTL_NAP);
                if (warp == 9) {
                    const int sum = (int)ld_rlx(reinterpret_cast<const uint32_t*>(cword) + 1);
                    if (lane == 0) ctl[16] = (uint32_t)max(min(((sum >> 6) * CTL_GAIN) >> 8, 20000), -20000);
                }
            }
        }
        const int ridx = 2 * (cta & (NSRC - 1)) + (warp - 9);
        if (ridx < NRED) {
            uint32_t* rin = rbox + ((br * NRED + ridx) * NSRC + (lane >> 2)) * 16 + (lane & 3) * 4;
            uint32_t* outp = reinterpret_cast<uint32_t*>(P.out + br * D_MODEL + ridx * 16) + (lane & 7);
            const bool hi = lane & 4;
            uint4 r[4];
            unsigned n = 0;
            float a0, a1, a2, a3;
            auto take = [&](const uint4 (&v)[4]) {
                a0 = (dec(v[0].x) + dec(v[1].x)) + (dec(v[2].x) + dec(v[3].x));
                a1 = (dec(v[0].y) + dec(v[1].y)) + (dec(v[2].y) + dec(v[3].y));
                a2 = (dec(v[0].z) + dec(v[1].z)) + (dec(v[2].z) + dec(v[3].z));
                a3 = (dec(v[0].w) + dec(v[1].w)) + (dec(v[2].w) + dec(v[3].w));
                return __all_sync(0xffffffffu, min(min(min4(v[0]), min4(v[1])), min(min4(v[2]), min4(v[3]))) != 0);
            };
#pragma unroll 1
            do {
#pragma unroll
                for (int i = 0; i < 4; i++) r[i] = ld_rlx4(rin + i * 128);
            } while (!take(r) && ++n < SPIN_LIMIT);
            float lo = (hi ? a1 : a0) + __shfl_xor_sync(0xffffffffu, hi ? a0 : a1, 4);
            float up = (hi ? a3 : a2) + __shfl_xor_sync(0xffffffffu, hi ? a2 : a3, 4);
            lo += __shfl_xor_sync(0xffffffffu, lo, 8);  up += __shfl_xor_sync(0xffffffffu, up, 8);
            lo += __shfl_xor_sync(0xffffffffu, lo, 16); up += __shfl_xor_sync(0xffffffffu, up, 16);
            if (lane < 8) asm volatile("st.global.u32 [%0], %1;" ::"l"(outp), "r"(pack_bf16(lo, up)) : "memory");
#pragma unroll
            for (int i = 0; i < 4; i++) st_rlx4(rin + i * 128, 0u);
        }
        return;
    }

    {
        const int i8 = lane & 7;
        const uint32_t woff = sb + SM_RING + (8 * (lane >> 4) + i8) * WO_ROW_BYTES + warp * 128 + ((((lane >> 3) & 1) ^ i8) << 4);
        const uint32_t omask = (t == (g >> 1)) ? ((g & 1) ? 0xffff0000u : 0x0000ffffu) : 0u;
        uint32_t* rout = rbox + ((br * NRED + 4 * warp + t) * NSRC + (cta & (NSRC - 1))) * 16 + 2 * g;
        float c[4][4], c2[4][4];
#pragma unroll
        for (int i = 0; i < 4; i++) { c[i][0] = c[i][1] = c[i][2] = c[i][3] = 0.f; c2[i][0] = c2[i][1] = c2[i][2] = c2[i][3] = 0.f; }
        bar_sync(2, 288);
        const uint32_t* o32 = reinterpret_cast<const uint32_t*>(smem + SM_O);
        uint32_t ob[2 * WO_CHUNKS];
#pragma unroll
        for (int j = 0; j < 2 * WO_CHUNKS; j++) ob[j] = o32[4 * j + t] & omask;
#pragma unroll
        for (int ks = 0; ks < WO_CHUNKS - 2; ks += 2) {
            mbar_wait(bar_full + ((NKV + ks) % NS) * 8, ((NKV + ks) / NS) & 1);
            mbar_wait(bar_full + ((NKV + ks + 1) % NS) * 8, ((NKV + ks + 1) / NS) & 1);
            uint4 a[8];
#pragma unroll
            for (int j = 0; j < 8; j++) a[j] = ldsm4t((woff ^ ((j & 3) << 5)) + ((NKV + ks + (j >> 2)) % NS) * SLOT_BYTES);
#pragma unroll
            for (int j = 0; j < 4; j++) {
                mma16816(c[j], a[j].x, a[j].y, a[j].z, a[j].w, ob[2 * ks], ob[2 * ks + 1]);
                mma16816(c2[j], a[4 + j].x, a[4 + j].y, a[4 + j].z, a[4 + j].w, ob[2 * ks + 2], ob[2 * ks + 3]);
            }
        }
#pragma unroll
        for (int ks = WO_CHUNKS - 2; ks < WO_CHUNKS; ks++) {
            mbar_wait(bar_full + ((NKV + ks) % NS) * 8, ((NKV + ks) / NS) & 1);
#pragma unroll
            for (int j = 0; j < 4; j++) {
                const uint4 a = ldsm4t((woff ^ (j << 5)) + ((NKV + ks) % NS) * SLOT_BYTES);
                if (ks & 1) mma16816(c[j], a.x, a.y, a.z, a.w, ob[2 * ks], ob[2 * ks + 1]);
                else mma16816(c2[j], a.x, a.y, a.z, a.w, ob[2 * ks], ob[2 * ks + 1]);
            }
            if (ks == WO_CHUNKS - 2) {
#pragma unroll
                for (int j = 0; j < 4; j++) { c[j][0] += c2[j][0]; c[j][1] += c2[j][1]; c[j][2] += c2[j][2]; c[j][3] += c2[j][3]; }
            }
        }
        float r[8];
#pragma unroll
        for (int y = 0; y < 8; y++) r[y] = c[y >> 1][2 * (y & 1)] + c[y >> 1][2 * ((y ^ 1) & 1) + 1];
        r[0] += __shfl_xor_sync(0xffffffffu, r[2], 1);
        r[1] += __shfl_xor_sync(0xffffffffu, r[3], 1);
        r[4] += __shfl_xor_sync(0xffffffffu, r[6], 1);
        r[5] += __shfl_xor_sync(0xffffffffu, r[7], 1);
        r[0] += __shfl_xor_sync(0xffffffffu, r[4], 2);
        r[1] += __shfl_xor_sync(0xffffffffu, r[5], 2);
        st_rlx2(rout, enc(r[0]), enc(r[1]));
        if ((uint32_t)cold == 2 * NCTA - 1)
            asm volatile("st.relaxed.gpu.global.u64 [%0], %1;" ::"l"(cword), "l"(0ull) : "memory");
    }
}

}

extern "C" void kernel_launch(void* const* d_in, const int* in_sizes, int n_in, void* d_out, int out_size) {
    (void)in_sizes; (void)n_in; (void)out_size;
    typedef CUresult (*EncodeFn)(CUtensorMap*, CUtensorMapDataType, cuuint32_t, void*, const cuuint64_t*, const cuuint64_t*,
                                 const cuuint32_t*, const cuuint32_t*, CUtensorMapInterleave, CUtensorMapSwizzle,
                                 CUtensorMapL2promotion, CUtensorMapFloatOOBfill);
    static EncodeFn encode = nullptr;
    static uint32_t* mail = nullptr;
    static int dt = 655;
    if (!mail) {
        cudaFuncSetAttribute(gqa_decode_fused, cudaFuncAttributeMaxDynamicSharedMemorySize, SM_TOTAL);
        void* p = nullptr;
        cudaGetSymbolAddress(&p, g_mail);
        mail = (uint32_t*)p;
        cudaDriverEntryPointQueryResult qres;
        cudaGetDriverEntryPoint("cuTensorMapEncodeTiled", &p, cudaEnableDefault, &qres);
        encode = (EncodeFn)p;
        int dev = 0, khz = 0, bits = 0;
        cudaGetDevice(&dev);
        if (cudaDeviceGetAttribute(&khz, cudaDevAttrMemoryClockRate, dev) == cudaSuccess &&
            cudaDeviceGetAttribute(&bits, cudaDevAttrGlobalMemoryBusWidth, dev) == cudaSuccess && khz > 0 && bits > 0) {
            const double bytes_per_ns = 2.0 * khz * 1e-6 * bits / 8.0;
            dt = (int)(2.0 * NCTA * TILE_BYTES / (0.955 * bytes_per_ns) + 0.5);
        }
        (void)cudaGetLastError();
    }
    Params p;
    for (int b = 0; b < 2; b++) {
        p.x[b] = (const __nv_bfloat16*)d_in[5 * b + 0];
        p.k[b] = (const __nv_bfloat16*)d_in[5 * b + 1];
        p.v[b] = (const __nv_bfloat16*)d_in[5 * b + 2];
        p.wq[b] = (const __nv_bfloat16*)d_in[5 * b + 3];
        p.wo[b] = (const __nv_bfloat16*)d_in[5 * b + 4];
        const cuuint64_t dims[2] = {(cuuint64_t)QCOLS, (cuuint64_t)D_MODEL};
        const cuuint64_t strides[1] = {(cuuint64_t)QCOLS * 2};
        const cuuint32_t box[2] = {256, 36}, estr[2] = {1, 1};
        encode(&p.wq_map[b], CU_TENSOR_MAP_DATA_TYPE_BFLOAT16, 2, d_in[5 * b + 3], dims, strides, box, estr,
               CU_TENSOR_MAP_INTERLEAVE_NONE, CU_TENSOR_MAP_SWIZZLE_NONE, CU_TENSOR_MAP_L2_PROMOTION_NONE,
               CU_TENSOR_MAP_FLOAT_OOB_FILL_NONE);
    }
    p.out = (__nv_bfloat16*)d_out;
    p.mail = mail;
    p.dt = dt;
    p.t0 = dt * 9 / 2 - T0_LEAD;
    gqa_decode_fused<<<NCTA, NTHREADS, SM_TOTAL>>>(p);
}
```

```cpp
#include <cuda.h>
#include <cuda_runtime.h>
#include <cuda_bf16.h>
#include <stdint.h>

namespace {

constexpr int D_MODEL = 576;
constexpr int HKV = 16;
constexpr int SK = 8192;
constexpr int DH = 128;
constexpr int QCOLS = 4096;
constexpr int NSPLIT = 2;
constexpr int NCTA = 2 * HKV * NSPLIT;
constexpr int TILE_KEYS = 64;
constexpr int TILE_BYTES = TILE_KEYS * DH * 2;
constexpr int NTILES = SK / NSPLIT / TILE_KEYS;
constexpr int NKV = 2 * NTILES;
constexpr int PH = 4;
constexpr int PU = PH / 2;
static_assert(PH == 4 && NKV == 128, "the producer's tile order is written for this shape");
constexpr int NS = 12;
constexpr int WO_ROW_BYTES = D_MODEL * 2;
constexpr int WO_CHUNK_BYTES = 16 * WO_ROW_BYTES;
constexpr int WO_CHUNKS = 8;
constexpr int SLOT_BYTES = WO_CHUNK_BYTES;
constexpr int WQ_SLOT0 = NS - 8;
constexpr int QROWS_PER_CTA = D_MODEL / NSPLIT;
constexpr int NTHREADS = 352;
constexpr int NRED = 36;
constexpr int NSRC = HKV * NSPLIT;
constexpr unsigned SPIN_LIMIT = 1u << 19;

constexpr int LAT_TARGET = 1750;
constexpr int CTL_GAIN = 22;
constexpr int CTL_FIRST = 12, CTL_STOP = NKV - 8;
constexpr int CTL_NAP = 500;
constexpr int T0_LEAD = 900;
constexpr int PFN = 3;

constexpr int SM_RING = 0;
constexpr int SM_RED = SM_RING + NS * SLOT_BYTES;
constexpr int SM_PQ = SM_RED + 8 * 256 * 4;
constexpr int SM_PO = SM_PQ + 1024;
constexpr int SM_ML = SM_PO + 528;
constexpr int SM_Q = SM_ML + 128;
constexpr int SM_O = SM_Q;
constexpr int SM_BAR = SM_Q + 512;
constexpr int SM_CTL = SM_BAR + (2 * NS + 10) * 8;
constexpr int SM_TOTAL = SM_CTL + 80;
static_assert(SM_TOTAL <= 232448, "shared memory");

constexpr int RBOX_WORDS = 2 * NRED * NSRC * 16;
__device__ __align__(1024) uint32_t g_mail[RBOX_WORDS + 32];

struct Params {
    const __nv_bfloat16* wq[2];
    const __nv_bfloat16* x[2];
    const __nv_bfloat16* k[2];
    const __nv_bfloat16* v[2];
    const __nv_bfloat16* wo[2];
    __nv_bfloat16* out;
    uint32_t* mail;
    int dt, t0;
    CUtensorMap wq_map[2];
};

__device__ __forceinline__ uint32_t gtime32() { uint32_t t; asm volatile("mov.u32 %0, %globaltimer_lo;" : "=r"(t)); return t; }
__device__ __forceinline__ uint32_t smem_u32(const void* p) { return (uint32_t)__cvta_generic_to_shared(p); }
__device__ __forceinline__ void mbar_init(uint32_t bar, uint32_t cnt) {
    asm volatile("mbarrier.init.shared::cta.b64 [%0], %1;" ::"r"(bar), "r"(cnt) : "memory");
}
__device__ __forceinline__ void mbar_expect_tx(uint32_t bar, uint32_t bytes) {
    asm volatile("mbarrier.arrive.expect_tx.shared::cta.b64 _, [%0], %1;" ::"r"(bar), "r"(bytes) : "memory");
}
__device__ __forceinline__ void mbar_arrive(uint32_t bar) {
    asm volatile("mbarrier.arrive.shared::cta.b64 _, [%0];" ::"r"(bar) : "memory");
}
__device__ __forceinline__ void mbar_arrive_n(uint32_t bar, uint32_t n) {
    asm volatile("mbarrier.arrive.shared::cta.b64 _, [%0], %1;" ::"r"(bar), "r"(n) : "memory");
}
__device__ __forceinline__ void mbar_wait(uint32_t bar, uint32_t parity) {
    unsigned n = 0;
    uint32_t ok;
#pragma unroll 1
    do {
        asm volatile("{\n.reg .pred p;\nmbarrier.try_wait.parity.shared::cta.b64 p, [%1], %2;\nselp.u32 %0, 1, 0, p;\n}"
                     : "=r"(ok) : "r"(bar), "r"(parity) : "memory");
    } while (!ok && ++n <= SPIN_LIMIT);
}
__device__ __forceinline__ void mbar_wait_cluster(uint32_t bar, uint32_t parity) {
    unsigned n = 0;
    uint32_t ok;
#pragma unroll 1
    do {
        asm volatile("{\n.reg .pred p;\nmbarrier.try_wait.parity.acquire.cluster.shared::cta.b64 p, [%1], %2;\nselp.u32 %0, 1, 0, p;\n}"
                     : "=r"(ok) : "r"(bar), "r"(parity) : "memory");
    } while (!ok && ++n <= SPIN_LIMIT);
}
__device__ __forceinline__ void expect_and_copy(uint32_t dst, const void* src, uint32_t bytes, uint32_t bar, uint64_t pol) {
    asm volatile("{\n.reg .pred p;\nelect.sync _|p, 0xffffffff;\n"
                 "@p mbarrier.arrive.expect_tx.shared::cta.b64 _, [%3], %2;\n"
                 "@p cp.async.bulk.shared::cluster.global.mbarrier::complete_tx::bytes.L2::cache_hint [%0], [%1], %2, [%3], %4;\n}"
                 ::"r"(dst), "l"(src), "r"(bytes), "r"(bar), "l"(pol) : "memory");
}
__device__ __forceinline__ void expect_and_copy_2d(uint32_t dst, const CUtensorMap* map, int c0, int c1, uint32_t bar, uint64_t pol) {
    asm volatile("{\n.reg .pred p;\nelect.sync _|p, 0xffffffff;\n"
                 "@p mbarrier.arrive.expect_tx.shared::cta.b64 _, [%2], %6;\n"
                 "@p cp.async.bulk.tensor.2d.shared::cluster.global.mbarrier::complete_tx::bytes.L2::cache_hint [%0], [%1, {%3, %4}], [%2], %5;\n}"
                 ::"r"(dst), "l"(map), "r"(bar), "r"(c0), "r"(c1), "l"(pol), "n"(SLOT_BYTES) : "memory");
}
__device__ __forceinline__ void st_peer(uint32_t peer_addr, float v, uint32_t peer_bar) {
    asm volatile("st.async.shared::cluster.mbarrier::complete_tx::bytes.f32 [%0], %1, [%2];" ::"r"(peer_addr), "f"(v), "r"(peer_bar) : "memory");
}
__device__ __forceinline__ void bar_sync(int id, int n) { asm volatile("bar.sync %0, %1;" ::"r"(id), "r"(n) : "memory"); }
__device__ __forceinline__ void bar_arrive(int id, int n) { asm volatile("bar.arrive %0, %1;" ::"r"(id), "r"(n) : "memory"); }
__device__ __forceinline__ void cluster_arrive() { asm volatile("barrier.cluster.arrive.relaxed.aligned;" ::: "memory"); }
__device__ __forceinline__ void cluster_wait() { asm volatile("barrier.cluster.wait.acquire.aligned;" ::: "memory"); }

__device__ __forceinline__ uint4 lds128(uint32_t a) {
    uint4 v;
    asm volatile("ld.shared.v4.u32 {%0,%1,%2,%3}, [%4];" : "=r"(v.x), "=r"(v.y), "=r"(v.z), "=r"(v.w) : "r"(a) : "memory");
    return v;
}
__device__ __forceinline__ uint4 ldsm4t(uint32_t a) {
    uint4 v;
    asm volatile("ldmatrix.sync.aligned.m8n8.x4.trans.shared.b16 {%0,%1,%2,%3}, [%4];"
                 : "=r"(v.x), "=r"(v.y), "=r"(v.z), "=r"(v.w) : "r"(a) : "memory");
    return v;
}
__device__ __forceinline__ void mma16816(float (&c)[4], uint32_t a0, uint32_t a1, uint32_t a2, uint32_t a3, uint32_t b0, uint32_t b1) {
    asm volatile("mma.sync.aligned.m16n8k16.row.col.f32.bf16.bf16.f32 {%0,%1,%2,%3}, {%4,%5,%6,%7}, {%8,%9}, {%0,%1,%2,%3};"
                 : "+f"(c[0]), "+f"(c[1]), "+f"(c[2]), "+f"(c[3])
                 : "r"(a0), "r"(a1), "r"(a2), "r"(a3), "r"(b0), "r"(b1));
}
__device__ __forceinline__ uint32_t pack_bf16(float lo, float hi) {
    uint32_t r;
    asm("cvt.rn.bf16x2.f32 %0, %1, %2;" : "=r"(r) : "f"(hi), "f"(lo));
    return r;
}
__device__ __forceinline__ float ex2(float x) { float y; asm("ex2.approx.ftz.f32 %0, %1;" : "=f"(y) : "f"(x)); return y; }
__device__ __forceinline__ float bf_lo(uint32_t u) { return __uint_as_float(u << 16); }
__device__ __forceinline__ float bf_hi(uint32_t u) { return __uint_as_float(u & 0xffff0000u); }

__device__ __forceinline__ uint32_t enc(float f) { uint32_t u = ~__float_as_uint(f); return u ? u : 0x80000000u; }
__device__ __forceinline__ float dec(uint32_t u) { return __uint_as_float(~u); }
__device__ __forceinline__ void st_rlx2(uint32_t* p, uint32_t a, uint32_t b) { asm volatile("st.relaxed.gpu.global.v2.u32 [%0], {%1,%2};" ::"l"(p), "r"(a), "r"(b) : "memory"); }
__device__ __forceinline__ void st_rlx4(uint32_t* p, uint32_t a) { asm volatile("st.relaxed.gpu.global.v4.u32 [%0], {%1,%1,%1,%1};" ::"l"(p), "r"(a) : "memory"); }
__device__ __forceinline__ uint32_t ld_rlx(const uint32_t* p) { uint32_t v; asm volatile("ld.relaxed.gpu.global.u32 %0, [%1];" : "=r"(v) : "l"(p) : "memory"); return v; }
__device__ __forceinline__ uint4 ld_rlx4(const uint32_t* p) { uint4 v; asm volatile("ld.relaxed.gpu.global.v4.u32 {%0,%1,%2,%3}, [%4];" : "=r"(v.x), "=r"(v.y), "=r"(v.z), "=r"(v.w) : "l"(p) : "memory"); return v; }
__device__ __forceinline__ uint32_t min4(uint4 v) { return min(min(v.x, v.y), min(v.z, v.w)); }

constexpr float SCALE_LOG2E = 0.08838834764831845f * 1.4426950408889634f;

__global__ void __cluster_dims__(NSPLIT, 1, 1) __launch_bounds__(NTHREADS, 1) gqa_decode_fused(const __grid_constant__ Params P) {
    extern __shared__ __align__(1024) unsigned char smem[];
    const int tid = threadIdx.x;
    const int cta = blockIdx.x;
    const int group = cta >> 1, s = cta & 1;
    const int br = group >> 4, h = group & 15;
    {
        const __nv_bfloat16* w = P.wq[br] + (size_t)(s * QROWS_PER_CTA + (tid >> 2)) * QCOLS + h * 256 + (tid & 3) * 64;
#pragma unroll
        for (int i = 0; i < PFN; i++)
            if (tid < 256) asm volatile("prefetch.global.L2 [%0];" ::"l"(w + (size_t)i * 64 * QCOLS));
    }
    const int warp = __shfl_sync(0xffffffffu, tid >> 5, 0), lane = tid & 31;

    uint32_t sb;
    asm volatile("mov.u32 %0, %1;" : "=r"(sb) : "r"(smem_u32(smem)));
    const int g = lane >> 2, t = lane & 3;
    const uint32_t bar_full = sb + SM_BAR, bar_empty = bar_full + NS * 8, bar_wq = bar_empty + NS * 8;
    const uint32_t bar_pq = bar_wq + 8 * 8, bar_po = bar_pq + 8;
    float* red = reinterpret_cast<float*>(smem + SM_RED);
    volatile uint32_t* ctl = reinterpret_cast<volatile uint32_t*>(smem + SM_CTL);
    uint32_t* const rbox = P.mail;
    unsigned long long* const cword = reinterpret_cast<unsigned long long*>(P.mail + RBOX_WORDS);
    unsigned long long cold = 0;

    if (warp < 8) {
        const int grp = warp >> 2, w4 = warp & 3;
        const int row0 = s * QROWS_PER_CTA + grp * 36 + w4 * 9;
        const uint32_t wsm = sb + SM_RING + (WQ_SLOT0 + grp) * SLOT_BYTES + w4 * 9 * 512;
        const uint32_t wbar = bar_wq + grp * 8;
        const int xl = lane < 27 ? lane : 0;
        const float xv = __bfloat162float(P.x[br][row0 + 72 * (xl / 9) + xl % 9]);
        const float xw = __bfloat162float(P.x[br][row0 + 216 + (lane < 9 ? lane : 0)]);
        cluster_arrive();
        bar_sync(1, 288);
        float a[8];
#pragma unroll
        for (int j = 0; j < 8; j++) a[j] = 0.f;
#pragma unroll 1
        for (int j = 0; j < 4; j++) {
            mbar_wait(wbar + j * 16, 0);
            const float xs = j < 3 ? xv : xw;
            const int xb = j < 3 ? 9 * j : 0;
#pragma unroll
            for (int i = 0; i < 9; i++) {
                const uint4 w = lds128(wsm + j * 2 * SLOT_BYTES + i * 512 + lane * 16);
                const float xi = __shfl_sync(0xffffffffu, xs, xb + i);
                a[0] = fmaf(xi, bf_lo(w.x), a[0]); a[1] = fmaf(xi, bf_hi(w.x), a[1]);
                a[2] = fmaf(xi, bf_lo(w.y), a[2]); a[3] = fmaf(xi, bf_hi(w.y), a[3]);
                a[4] = fmaf(xi, bf_lo(w.z), a[4]); a[5] = fmaf(xi, bf_hi(w.z), a[5]);
                a[6] = fmaf(xi, bf_lo(w.w), a[6]); a[7] = fmaf(xi, bf_hi(w.w), a[7]);
            }
            __syncwarp();
            if (lane == 0) mbar_arrive(bar_empty + (WQ_SLOT0 + 2 * j + grp) * 8);
        }
        float4* dst = reinterpret_cast<float4*>(red + warp * 256 + lane * 8);
        dst[0] = make_float4(a[0], a[1], a[2], a[3]);
        dst[1] = make_float4(a[4], a[5], a[6], a[7]);
        cluster_wait();
        bar_sync(1, 256);
        uint32_t peer;
        asm volatile("mapa.shared::cluster.u32 %0, %1, %2;" : "=r"(peer) : "r"(sb), "r"(s ^ 1));
        {
            float part = 0.f;
#pragma unroll
            for (int w8 = 0; w8 < 8; w8++) part += red[w8 * 256 + tid];
            st_peer(peer + SM_PQ + tid * 4, part, peer + (bar_pq - sb));
            mbar_wait_cluster(bar_pq, 0);
            reinterpret_cast<__nv_bfloat16*>(smem + SM_Q)[tid] = __float2bfloat16(part + reinterpret_cast<const float*>(smem + SM_PQ)[tid]);
        }
        bar_sync(1, 256);

        uint4 qf[4];
#pragma unroll
        for (int j = 0; j < 4; j++)
            qf[j] = lds128(sb + SM_Q + (g & 1) * 256 + ((4 * (j ^ (g >> 2)) + t) << 4));

        const uint32_t koffA = (w4 * 16 + g) * 256 + t * 16 + (g & 1) * 64;
        const uint32_t koffB = (w4 * 16 + g) * 256 + t * 16 + ((g & 1) ^ 1) * 64;
        const int vi = lane & 7;
        const int vkey = 8 * (lane >> 4) + ((vi < 4) ? 2 * vi : 2 * (vi - 4) + 1);
        const uint32_t voff = (w4 * 16 + vkey) * 256 + ((((lane >> 3) & 1) ^ vi) << 4);
        const int kap = (g >> 1) | ((g & 1) << 2);
        const bool valid = (t >> 1) == (g & 1);
        const uint32_t amask = (t == (kap >> 1)) ? ((kap & 1) ? 0xffff0000u : 0x0000ffffu) : 0u;

        float acc[16][4];
#pragma unroll
        for (int i = 0; i < 16; i++) { acc[i][0] = acc[i][1] = acc[i][2] = acc[i][3] = 0.f; }
        float m0 = -INFINITY, m1 = -INFINITY, l0 = 0.f, l1 = 0.f;
        uint32_t fbar = bar_full + grp * 8, tbase = sb + SM_RING + grp * SLOT_BYTES, ph = 0;
        auto advance = [&]() {
            __syncwarp();
            if (lane == 0) mbar_arrive(fbar + NS * 8);
            fbar += 16; tbase += 2 * SLOT_BYTES;
            if (fbar >= bar_empty) { fbar -= NS * 8; tbase -= NS * SLOT_BYTES; ph ^= 1; }
        };
        auto sample = [&](int i) {
            if ((tid & 127) == 0 && i >= CTL_FIRST && i < CTL_STOP + 4) {
                int e = (int)(gtime32() - ctl[i & 15]) - LAT_TARGET;
                e = max(min(e, 2000), -1000);
                if (i < CTL_STOP)
                    asm volatile("red.relaxed.gpu.global.add.u64 [%0], %1;" ::"l"(cword), "l"((unsigned long long)(long long)e << 32) : "memory");
                else
                    asm volatile("atom.relaxed.gpu.global.add.u64 %0, [%1], %2;" : "=l"(cold) : "l"(cword), "l"(1ull) : "memory");
            }
        };
#pragma unroll 1
        for (int it = 0; it < NTILES / PH; it++) {
            float sv[PU][4];
#pragma unroll
            for (int u = 0; u < PU; u++) {
                mbar_wait(fbar, ph);
                if (u & 1) sample(2 * PH * it + 2 * u + grp);
                float sa[4] = {0.f, 0.f, 0.f, 0.f}, sc[4] = {0.f, 0.f, 0.f, 0.f};
                uint4 L[4], H[4];
                L[0] = lds128(tbase + koffA);       H[0] = lds128(tbase + koffA + 2048);
                L[1] = lds128(tbase + koffB);       H[1] = lds128(tbase + koffB + 2048);
                L[2] = lds128(tbase + koffA + 128); H[2] = lds128(tbase + koffA + 128 + 2048);
                L[3] = lds128(tbase + koffB + 128); H[3] = lds128(tbase + koffB + 128 + 2048);
#pragma unroll
                for (int j = 0; j < 4; j++) {
                    mma16816(sa, L[j].x, H[j].x, L[j].y, H[j].y, qf[j].x, qf[j].y);
                    mma16816(sc, L[j].z, H[j].z, L[j].w, H[j].w, qf[j].z, qf[j].w);
                }
                advance();
#pragma unroll
                for (int e = 0; e < 4; e++) sv[u][e] = valid ? sa[e] + sc[e] : -INFINITY;
            }
            float x0 = fmaxf(sv[0][0], sv[0][2]), x1 = fmaxf(sv[0][1], sv[0][3]);
#pragma unroll
            for (int u = 1; u < PU; u++) { x0 = fmaxf(x0, fmaxf(sv[u][0], sv[u][2])); x1 = fmaxf(x1, fmaxf(sv[u][1], sv[u][3])); }
#pragma unroll
            for (int o = 2; o <= 16; o <<= 1) {
                x0 = fmaxf(x0, __shfl_xor_sync(0xffffffffu, x0, o));
                x1 = fmaxf(x1, __shfl_xor_sync(0xffffffffu, x1, o));
            }
            if (x0 > m0 || x1 > m1) {
                const float n0 = fmaxf(m0, x0), n1 = fmaxf(m1, x1);
                const float a0 = ex2((m0 - n0) * SCALE_LOG2E), a1 = ex2((m1 - n1) * SCALE_LOG2E);
                m0 = n0; m1 = n1;
                l0 *= a0; l1 *= a1;
#pragma unroll
                for (int i = 0; i < 8; i++) {
                    acc[i][0] *= a0; acc[i][1] *= a0; acc[i][2] *= a0; acc[i][3] *= a0;
                    acc[8 + i][0] *= a1; acc[8 + i][1] *= a1; acc[8 + i][2] *= a1; acc[8 + i][3] *= a1;
                }
            }
            uint32_t pb[PU][4];
#pragma unroll
            for (int u = 0; u < PU; u++) {
                const float p0 = ex2((sv[u][0] - m0) * SCALE_LOG2E), p1 = ex2((sv[u][1] - m1) * SCALE_LOG2E);
                const float p2 = ex2((sv[u][2] - m0) * SCALE_LOG2E), p3 = ex2((sv[u][3] - m1) * SCALE_LOG2E);
                l0 += p0 + p2; l1 += p1 + p3;
                pb[u][0] = pack_bf16(p0, p0) & amask; pb[u][1] = pack_bf16(p1, p1) & amask;
                pb[u][2] = pack_bf16(p2, p2) & amask; pb[u][3] = pack_bf16(p3, p3) & amask;
            }
#pragma unroll
            for (int u = 0; u < PU; u++) {
                mbar_wait(fbar, ph);
                if (u & 1) sample(2 * PH * it + PH + 2 * u + grp);
#pragma unroll
                for (int j = 0; j < 8; j++) {
                    const uint4 a = ldsm4t(tbase + (voff ^ ((j & 3) << 5)) + (j >> 2) * 128);
                    mma16816(acc[j], a.x, a.y, a.z, a.w, pb[u][0], pb[u][2]);
                    mma16816(acc[8 + j], a.x, a.y, a.z, a.w, pb[u][1], pb[u][3]);
                }
                advance();
            }
        }

#pragma unroll
        for (int q = 0; q < 4; q++) {
            float r[8];
#pragma unroll
            for (int y = 0; y < 8; y++) r[y] = acc[4 * q + (y >> 1)][2 * (y & 1)] + acc[4 * q + ((y ^ 4) >> 1)][2 * (y & 1) + 1];
#pragma unroll
            for (int y = 0; y < 8; y += 2) r[y] += __shfl_xor_sync(0xffffffffu, r[y + 1], 1);
            r[0] += __shfl_xor_sync(0xffffffffu, r[2], 2);
            r[4] += __shfl_xor_sync(0xffffffffu, r[6], 2);
            float* dst2 = red + warp * 256 + q * 64 + t * 8 + g;
            dst2[0] = r[0];
            dst2[32] = r[4];
        }
#pragma unroll
        for (int o = 2; o <= 16; o <<= 1) {
            l0 += __shfl_xor_sync(0xffffffffu, l0, o);
            l1 += __shfl_xor_sync(0xffffffffu, l1, o);
        }
        float* ml = reinterpret_cast<float*>(smem + SM_ML);
        if (lane == 0) *reinterpret_cast<float4*>(ml + warp * 4) = make_float4(m0, l0, m1, l1);
        bar_sync(1, 256);
        {
            const int hd = tid >> 7;
            float2 w[8];
#pragma unroll
            for (int i = 0; i < 8; i++) w[i] = *reinterpret_cast<const float2*>(ml + i * 4 + hd * 2);
            float M = w[0].x;
#pragma unroll
            for (int i = 1; i < 8; i++) M = fmaxf(M, w[i].x);
            float o = 0.f, L = 0.f;
#pragma unroll
            for (int i = 0; i < 8; i++) {
                const float f = ex2((w[i].x - M) * SCALE_LOG2E);
                o = fmaf(f, red[i * 256 + tid], o);
                L = fmaf(f, w[i].y, L);
            }
            const int d = tid & 127;
            if (hd != s) {
                st_peer(peer + SM_PO + d * 4, o, peer + (bar_po - sb));
                if (d < 2) st_peer(peer + SM_PO + 512 + d * 4, d ? L : M, peer + (bar_po - sb));
            } else {
                mbar_wait_cluster(bar_po, 0);
                const float* pbuf = reinterpret_cast<const float*>(smem + SM_PO);
                const float Mp = pbuf[128], Lp = pbuf[129];
                const float Mx = fmaxf(M, Mp);
                const float f = ex2((M - Mx) * SCALE_LOG2E), fp = ex2((Mp - Mx) * SCALE_LOG2E);
                reinterpret_cast<__nv_bfloat16*>(smem + SM_O)[d] = __float2bfloat16(__fdividef(f * o + fp * pbuf[d], f * L + fp * Lp));
            }
        }
    } else if (warp == 8) {
        const uint32_t t_entry = gtime32();
        if (lane == 0) {
            asm volatile("prefetch.param.tensormap [%0];" ::"l"(__cvta_generic_to_grid_constant(&P.wq_map[br])) : "memory");
#pragma unroll
            for (int i = 0; i < 8; i++) mbar_init(bar_wq + i * 8, 1);
            asm volatile("fence.mbarrier_init.release.cluster;" ::: "memory");
        }
        __syncwarp();
        uint64_t pol;
        asm volatile("createpolicy.fractional.L2::evict_first.b64 %0, 1.0;" : "=l"(pol));
#pragma unroll
        for (int c = 0; c < 4; c++)
            expect_and_copy_2d(sb + SM_RING + (WQ_SLOT0 + c) * SLOT_BYTES, &P.wq_map[br], h * 256, s * QROWS_PER_CTA + c * 36, bar_wq + c * 8, pol);
        if (lane == 0) {
#pragma unroll
            for (int i = 0; i < 2 * NS; i++) mbar_init(bar_full + i * 8, i >= NS ? 4 : 1);
            mbar_init(bar_pq, 1);
            mbar_init(bar_po, 1);
            asm volatile("fence.mbarrier_init.release.cluster;" ::: "memory");
            mbar_expect_tx(bar_pq, 256 * 4);
            mbar_expect_tx(bar_po, 130 * 4);
#pragma unroll
            for (int i = 0; i < WQ_SLOT0; i++) mbar_arrive_n(bar_empty + i * 8, 4);
            ctl[16] = 0; ctl[17] = 0;
        }
        __syncwarp();
        cluster_arrive();
        bar_arrive(1, 288);
        bar_arrive(3, 96);
#pragma unroll
        for (int c = 4; c < 8; c++)
            expect_and_copy_2d(sb + SM_RING + (WQ_SLOT0 + c) * SLOT_BYTES, &P.wq_map[br], h * 256, s * QROWS_PER_CTA + c * 36, bar_wq + c * 8, pol);
        const size_t off = (size_t)h * SK * DH + (size_t)s * 8 * TILE_KEYS * DH;
        const unsigned char* kp = reinterpret_cast<const unsigned char*>(P.k[br] + off);
        const unsigned char* vp = reinterpret_cast<const unsigned char*>(P.v[br] + off);
        const unsigned char* wop = reinterpret_cast<const unsigned char*>(P.wo[br] + (size_t)(h * 256 + s * 128) * D_MODEL);
        if (lane == 0) {
            asm volatile("cp.async.bulk.prefetch.L2.global [%0], 16;" ::"l"(kp));
            asm volatile("cp.async.bulk.prefetch.L2.global [%0], 16;" ::"l"(vp));
            asm volatile("cp.async.bulk.prefetch.L2.global [%0], 16;" ::"l"(wop));
            asm volatile("cp.async.bulk.prefetch.L2.global [%0], 16;" ::"l"(wop + WO_CHUNKS * WO_CHUNK_BYTES - 16));
        }
        __syncwarp();
        const int dt = P.dt, dtw = dt + (dt >> 3);
        uint32_t tnext = 2 * P.t0 + ((cta * dt) >> 6);
        uint32_t sbar = bar_full, sdst = sb + SM_RING, eph = 0;
#pragma unroll 1
        for (int i = 0; i < NKV + WO_CHUNKS; i++) {
            const bool isw = i >= NKV;
            const int tile = ((i >> 3) & 7) * 16 + (i >> 6) * 4 + (i & 3);
            const unsigned char* src = isw ? wop + (i - NKV) * WO_CHUNK_BYTES : ((i & 4) ? vp : kp) + tile * TILE_BYTES;
            mbar_wait(sbar + NS * 8, eph);
            unsigned n = 0;
            uint32_t now;
            const uint32_t due = t_entry + (tnext >> 1);
#pragma unroll 1
            do { now = gtime32(); } while ((int)(now - due - ctl[16]) < 0 && ++n < SPIN_LIMIT);
            if (lane == 0) ctl[i & 15] = now;
            expect_and_copy(sdst, src, isw ? WO_CHUNK_BYTES : TILE_BYTES, sbar, pol);
            tnext += isw ? dtw : dt;
            sbar += 8; sdst += SLOT_BYTES;
            if (sbar == bar_empty) { sbar = bar_full; sdst = sb + SM_RING; eph ^= 1; }
            if (i == CTL_STOP && lane == 0) ctl[17] = 1;
        }
        cluster_wait();
    } else {
        cluster_arrive();
        bar_sync(3, 96);
        cluster_wait();
        {
            unsigned n = 0;
#pragma unroll 1
            while (ctl[17] == 0 && ++n < SPIN_LIMIT) {
                __nanosleep(CTL_NAP);
                if (warp == 9) {
                    const int sum = (int)ld_rlx(reinterpret_cast<const uint32_t*>(cword) + 1);
                    if (lane == 0) ctl[16] = (uint32_t)max(min(((sum >> 6) * CTL_GAIN) >> 8, 20000), -20000);
                }
            }
        }
        const int ridx = 2 * (cta & (NSRC - 1)) + (warp - 9);
        if (ridx < NRED) {
            uint32_t* rin = rbox + ((br * NRED + ridx) * NSRC + (lane >> 2)) * 16 + (lane & 3) * 4;
            uint32_t* outp = reinterpret_cast<uint32_t*>(P.out + br * D_MODEL + ridx * 16) + (lane & 7);
            const bool hi = lane & 4;
            uint4 r[4];
            unsigned n = 0;
            float a0, a1, a2, a3;
            auto take = [&](const uint4 (&v)[4]) {
                a0 = (dec(v[0].x) + dec(v[1].x)) + (dec(v[2].x) + dec(v[3].x));
                a1 = (dec(v[0].y) + dec(v[1].y)) + (dec(v[2].y) + dec(v[3].y));
                a2 = (dec(v[0].z) + dec(v[1].z)) + (dec(v[2].z) + dec(v[3].z));
                a3 = (dec(v[0].w) + dec(v[1].w)) + (dec(v[2].w) + dec(v[3].w));
                return __all_sync(0xffffffffu, min(min(min4(v[0]), min4(v[1])), min(min4(v[2]), min4(v[3]))) != 0);
            };
#pragma unroll 1
            do {
#pragma unroll
                for (int i = 0; i < 4; i++) r[i] = ld_rlx4(rin + i * 128);
            } while (!take(r) && ++n < SPIN_LIMIT);
            float lo = (hi ? a1 : a0) + __shfl_xor_sync(0xffffffffu, hi ? a0 : a1, 4);
            float up = (hi ? a3 : a2) + __shfl_xor_sync(0xffffffffu, hi ? a2 : a3, 4);
            lo += __shfl_xor_sync(0xffffffffu, lo, 8);  up += __shfl_xor_sync(0xffffffffu, up, 8);
            lo += __shfl_xor_sync(0xffffffffu, lo, 16); up += __shfl_xor_sync(0xffffffffu, up, 16);
            if (lane < 8) asm volatile("st.global.u32 [%0], %1;" ::"l"(outp), "r"(pack_bf16(lo, up)) : "memory");
#pragma unroll
            for (int i = 0; i < 4; i++) st_rlx4(rin + i * 128, 0u);
        }
        return;
    }

    {
        const int i8 = lane & 7;
        const uint32_t woff = sb + SM_RING + (8 * (lane >> 4) + i8) * WO_ROW_BYTES + warp * 128 + ((((lane >> 3) & 1) ^ i8) << 4);
        const uint32_t omask = (t == (g >> 1)) ? ((g & 1) ? 0xffff0000u : 0x0000ffffu) : 0u;
        uint32_t* rout = rbox + ((br * NRED + 4 * warp + t) * NSRC + (cta & (NSRC - 1))) * 16 + 2 * g;
        float c[4][4], c2[4][4];
#pragma unroll
        for (int i = 0; i < 4; i++) { c[i][0] = c[i][1] = c[i][2] = c[i][3] = 0.f; c2[i][0] = c2[i][1] = c2[i][2] = c2[i][3] = 0.f; }
        bar_sync(2, 288);
        const uint32_t* o32 = reinterpret_cast<const uint32_t*>(smem + SM_O);
        uint32_t ob[2 * WO_CHUNKS];
#pragma unroll
        for (int j = 0; j < 2 * WO_CHUNKS; j++) ob[j] = o32[4 * j + t] & omask;
#pragma unroll
        for (int ks = 0; ks < WO_CHUNKS - 2; ks += 2) {
            mbar_wait(bar_full + ((NKV + ks) % NS) * 8, ((NKV + ks) / NS) & 1);
            mbar_wait(bar_full + ((NKV + ks + 1) % NS) * 8, ((NKV + ks + 1) / NS) & 1);
            uint4 a[8];
#pragma unroll
            for (int j = 0; j < 8; j++) a[j] = ldsm4t((woff ^ ((j & 3) << 5)) + ((NKV + ks + (j >> 2)) % NS) * SLOT_BYTES);
#pragma unroll
            for (int j = 0; j < 4; j++) {
                mma16816(c[j], a[j].x, a[j].y, a[j].z, a[j].w, ob[2 * ks], ob[2 * ks + 1]);
                mma16816(c2[j], a[4 + j].x, a[4 + j].y, a[4 + j].z, a[4 + j].w, ob[2 * ks + 2], ob[2 * ks + 3]);
            }
        }
#pragma unroll
        for (int ks = WO_CHUNKS - 2; ks < WO_CHUNKS; ks++) {
            mbar_wait(bar_full + ((NKV + ks) % NS) * 8, ((NKV + ks) / NS) & 1);
#pragma unroll
            for (int j = 0; j < 4; j++) {
                const uint4 a = ldsm4t((woff ^ (j << 5)) + ((NKV + ks) % NS) * SLOT_BYTES);
                if (ks & 1) mma16816(c[j], a.x, a.y, a.z, a.w, ob[2 * ks], ob[2 * ks + 1]);
                else mma16816(c2[j], a.x, a.y, a.z, a.w, ob[2 * ks], ob[2 * ks + 1]);
            }
            if (ks == WO_CHUNKS - 2) {
#pragma unroll
                for (int j = 0; j < 4; j++) { c[j][0] += c2[j][0]; c[j][1] += c2[j][1]; c[j][2] += c2[j][2]; c[j][3] += c2[j][3]; }
            }
        }
        float r[8];
#pragma unroll
        for (int y = 0; y < 8; y++) r[y] = c[y >> 1][2 * (y & 1)] + c[y >> 1][2 * ((y ^ 1) & 1) + 1];
        r[0] += __shfl_xor_sync(0xffffffffu, r[2], 1);
        r[1] += __shfl_xor_sync(0xffffffffu, r[3], 1);
        r[4] += __shfl_xor_sync(0xffffffffu, r[6], 1);
        r[5] += __shfl_xor_sync(0xffffffffu, r[7], 1);
        r[0] += __shfl_xor_sync(0xffffffffu, r[4], 2);
        r[1] += __shfl_xor_sync(0xffffffffu, r[5], 2);
        st_rlx2(rout, enc(r[0]), enc(r[1]));
        if ((uint32_t)cold == 2 * NCTA - 1)
            asm volatile("st.relaxed.gpu.global.u64 [%0], %1;" ::"l"(cword), "l"(0ull) : "memory");
    }
}

}

extern "C" void kernel_launch(void* const* d_in, const int* in_sizes, int n_in, void* d_out, int out_size) {
    (void)in_sizes; (void)n_in; (void)out_size;
    typedef CUresult (*EncodeFn)(CUtensorMap*, CUtensorMapDataType, cuuint32_t, void*, const cuuint64_t*, const cuuint64_t*,
                                 const cuuint32_t*, const cuuint32_t*, CUtensorMapInterleave, CUtensorMapSwizzle,
                                 CUtensorMapL2promotion, CUtensorMapFloatOOBfill);
    static EncodeFn encode = nullptr;
    static uint32_t* mail = nullptr;
    static int dt = 655;
    if (!mail) {
        cudaFuncSetAttribute(gqa_decode_fused, cudaFuncAttributeMaxDynamicSharedMemorySize, SM_TOTAL);
        void* p = nullptr;
        cudaGetSymbolAddress(&p, g_mail);
        mail = (uint32_t*)p;
        cudaDriverEntryPointQueryResult qres = cudaDriverEntryPointSymbolNotFound;
        cudaGetDriverEntryPoint("cuTensorMapEncodeTiled", &p, cudaEnableDefault, &qres);
        encode = (qres == cudaDriverEntryPointSuccess) ? (EncodeFn)p : nullptr;
        int dev = 0, khz = 0, bits = 0;
        cudaGetDevice(&dev);
        if (cudaDeviceGetAttribute(&khz, cudaDevAttrMemoryClockRate, dev) == cudaSuccess &&
            cudaDeviceGetAttribute(&bits, cudaDevAttrGlobalMemoryBusWidth, dev) == cudaSuccess && khz > 0 && bits > 0) {
            const double bytes_per_ns = 2.0 * khz * 1e-6 * bits / 8.0;
            dt = (int)(2.0 * NCTA * TILE_BYTES / (0.955 * bytes_per_ns) + 0.5);
        }
        (void)cudaGetLastError();
    }
    if (!encode) return;
    Params p;
    for (int b = 0; b < 2; b++) {
        p.x[b] = (const __nv_bfloat16*)d_in[5 * b + 0];
        p.k[b] = (const __nv_bfloat16*)d_in[5 * b + 1];
        p.v[b] = (const __nv_bfloat16*)d_in[5 * b + 2];
        p.wq[b] = (const __nv_bfloat16*)d_in[5 * b + 3];
        p.wo[b] = (const __nv_bfloat16*)d_in[5 * b + 4];
        const cuuint64_t dims[2] = {(cuuint64_t)QCOLS, (cuuint64_t)D_MODEL};
        const cuuint64_t strides[1] = {(cuuint64_t)QCOLS * 2};
        const cuuint32_t box[2] = {256, 36}, estr[2] = {1, 1};
        encode(&p.wq_map[b], CU_TENSOR_MAP_DATA_TYPE_BFLOAT16, 2, d_in[5 * b + 3], dims, strides, box, estr,
               CU_TENSOR_MAP_INTERLEAVE_NONE, CU_TENSOR_MAP_SWIZZLE_NONE, CU_TENSOR_MAP_L2_PROMOTION_NONE,
               CU_TENSOR_MAP_FLOAT_OOB_FILL_NONE);
    }
    p.out = (__nv_bfloat16*)d_out;
    p.mail = mail;
    p.dt = dt;
    p.t0 = dt * 9 / 2 > T0_LEAD ? dt * 9 / 2 - T0_LEAD : 0;
    gqa_decode_fused<<<NCTA, NTHREADS, SM_TOTAL>>>(p);
}
```

```cpp
#include <cuda.h>
#include <cuda_runtime.h>
#include <cuda_bf16.h>
#include <stdint.h>

namespace {

constexpr int D_MODEL = 576;
constexpr int HKV = 16;
constexpr int SK = 8192;
constexpr int DH = 128;
constexpr int QCOLS = 4096;
constexpr int NSPLIT = 2;
constexpr int NCTA = 2 * HKV * NSPLIT;
constexpr int TILE_KEYS = 64;
constexpr int TILE_BYTES = TILE_KEYS * DH * 2;
constexpr int NKV = 2 * (8 + HKV * 4);
constexpr int N0 = 2, N1 = 2;
constexpr int NPH = HKV + 3;
constexpr int OWN_TILE0 = 112;
static_assert(SK / TILE_KEYS == 128, "the phase schedule is written for this shape");
constexpr int NS = 12;
constexpr int WO_ROW_BYTES = D_MODEL * 2;
constexpr int WO_CHUNK_BYTES = 16 * WO_ROW_BYTES;
constexpr int WO_CHUNKS = 8;
constexpr int SLOT_BYTES = WO_CHUNK_BYTES;
constexpr int WQ_SLOT0 = NS - 8;
constexpr int QROWS_PER_CTA = D_MODEL / NSPLIT;
constexpr int NTHREADS = 384;
constexpr int NRED = 36;
constexpr int NSRC = HKV * NSPLIT;
constexpr unsigned SPIN_LIMIT = 1u << 19;

constexpr int LAT_TARGET = 1650;
constexpr int CTL_GAIN = 36;
constexpr int CTL_LAST = NPH - 3;
constexpr int CTL_NAP = 800;
constexpr int T0_LEAD = 875;
constexpr int PFN = 3;

constexpr int SM_RING = 0;
constexpr int SM_RED = SM_RING + NS * SLOT_BYTES;
constexpr int SM_PQ = SM_RED + 8 * 256 * 4;
constexpr int SM_PO = SM_PQ + 1024;
constexpr int SM_ML = SM_PO + 528;
constexpr int SM_Q = SM_ML + 128;
constexpr int SM_O = SM_Q;
constexpr int SM_BAR = SM_Q + 512;
constexpr int SM_G = SM_RING + (NS - 1) * SLOT_BYTES + TILE_BYTES;
constexpr int SM_TAB = SM_BAR + (2 * NS + 17) * 8;
constexpr int SM_CTL = SM_TAB + 296;
static_assert(NKV % NS + WO_CHUNKS < NS, "wo must not use the last slot");
constexpr int SM_TOTAL = SM_CTL + 80;
static_assert(SM_TOTAL <= 232448, "shared memory");

constexpr int RBOX_WORDS = 2 * NRED * NSRC * 16;
constexpr int QBOX_WORDS = NCTA * HKV * 128;
constexpr int OBOX_WORDS = NCTA * NSRC * 128;
constexpr int MBOX_WORDS = NCTA * NSRC * 2;
constexpr int CW_OFF = RBOX_WORDS, MB_OFF = CW_OFF + 32, QB_OFF = MB_OFF + MBOX_WORDS, OB_OFF = QB_OFF + QBOX_WORDS;
__device__ __align__(1024) uint32_t g_mail[OB_OFF + OBOX_WORDS];

struct Params {
    const __nv_bfloat16* wq[2];
    const __nv_bfloat16* x[2];
    const __nv_bfloat16* k[2];
    const __nv_bfloat16* v[2];
    const __nv_bfloat16* wo[2];
    __nv_bfloat16* out;
    uint32_t* mail;
    int dt, t0;
    CUtensorMap wq_map[2];
};

__device__ __forceinline__ uint32_t gtime32() { uint32_t t; asm volatile("mov.u32 %0, %globaltimer_lo;" : "=r"(t)); return t; }
__device__ __forceinline__ uint32_t smem_u32(const void* p) { return (uint32_t)__cvta_generic_to_shared(p); }
__device__ __forceinline__ void mbar_init(uint32_t bar, uint32_t cnt) {
    asm volatile("mbarrier.init.shared::cta.b64 [%0], %1;" ::"r"(bar), "r"(cnt) : "memory");
}
__device__ __forceinline__ void mbar_expect_tx(uint32_t bar, uint32_t bytes) {
    asm volatile("mbarrier.arrive.expect_tx.shared::cta.b64 _, [%0], %1;" ::"r"(bar), "r"(bytes) : "memory");
}
__device__ __forceinline__ void mbar_arrive(uint32_t bar) {
    asm volatile("mbarrier.arrive.shared::cta.b64 _, [%0];" ::"r"(bar) : "memory");
}
__device__ __forceinline__ void mbar_arrive_n(uint32_t bar, uint32_t n) {
    asm volatile("mbarrier.arrive.shared::cta.b64 _, [%0], %1;" ::"r"(bar), "r"(n) : "memory");
}
__device__ __forceinline__ void mbar_wait(uint32_t bar, uint32_t parity) {
    unsigned n = 0;
    uint32_t ok;
#pragma unroll 1
    do {
        asm volatile("{\n.reg .pred p;\nmbarrier.try_wait.parity.shared::cta.b64 p, [%1], %2;\nselp.u32 %0, 1, 0, p;\n}"
                     : "=r"(ok) : "r"(bar), "r"(parity) : "memory");
    } while (!ok && ++n <= SPIN_LIMIT);
}
__device__ __forceinline__ void mbar_wait_cluster(uint32_t bar, uint32_t parity) {
    unsigned n = 0;
    uint32_t ok;
#pragma unroll 1
    do {
        asm volatile("{\n.reg .pred p;\nmbarrier.try_wait.parity.acquire.cluster.shared::cta.b64 p, [%1], %2;\nselp.u32 %0, 1, 0, p;\n}"
                     : "=r"(ok) : "r"(bar), "r"(parity) : "memory");
    } while (!ok && ++n <= SPIN_LIMIT);
}
__device__ __forceinline__ void expect_and_copy(uint32_t dst, const void* src, uint32_t bytes, uint32_t bar, uint64_t pol) {
    asm volatile("{\n.reg .pred p;\nelect.sync _|p, 0xffffffff;\n"
                 "@p mbarrier.arrive.expect_tx.shared::cta.b64 _, [%3], %2;\n"
                 "@p cp.async.bulk.shared::cluster.global.mbarrier::complete_tx::bytes.L2::cache_hint [%0], [%1], %2, [%3], %4;\n}"
                 ::"r"(dst), "l"(src), "r"(bytes), "r"(bar), "l"(pol) : "memory");
}
__device__ __forceinline__ void expect_and_copy_2d(uint32_t dst, const CUtensorMap* map, int c0, int c1, uint32_t bar, uint64_t pol) {
    asm volatile("{\n.reg .pred p;\nelect.sync _|p, 0xffffffff;\n"
                 "@p mbarrier.arrive.expect_tx.shared::cta.b64 _, [%2], %6;\n"
                 "@p cp.async.bulk.tensor.2d.shared::cluster.global.mbarrier::complete_tx::bytes.L2::cache_hint [%0], [%1, {%3, %4}], [%2], %5;\n}"
                 ::"r"(dst), "l"(map), "r"(bar), "r"(c0), "r"(c1), "l"(pol), "n"(SLOT_BYTES) : "memory");
}
__device__ __forceinline__ void st_peer(uint32_t peer_addr, float v, uint32_t peer_bar) {
    asm volatile("st.async.shared::cluster.mbarrier::complete_tx::bytes.f32 [%0], %1, [%2];" ::"r"(peer_addr), "f"(v), "r"(peer_bar) : "memory");
}
__device__ __forceinline__ void bar_sync(int id, int n) { asm volatile("bar.sync %0, %1;" ::"r"(id), "r"(n) : "memory"); }
__device__ __forceinline__ void bar_arrive(int id, int n) { asm volatile("bar.arrive %0, %1;" ::"r"(id), "r"(n) : "memory"); }
__device__ __forceinline__ void cluster_arrive() { asm volatile("barrier.cluster.arrive.relaxed.aligned;" ::: "memory"); }
__device__ __forceinline__ void cluster_wait() { asm volatile("barrier.cluster.wait.acquire.aligned;" ::: "memory"); }

__device__ __forceinline__ uint4 lds128(uint32_t a) {
    uint4 v;
    asm volatile("ld.shared.v4.u32 {%0,%1,%2,%3}, [%4];" : "=r"(v.x), "=r"(v.y), "=r"(v.z), "=r"(v.w) : "r"(a) : "memory");
    return v;
}
__device__ __forceinline__ uint4 ldsm4t(uint32_t a) {
    uint4 v;
    asm volatile("ldmatrix.sync.aligned.m8n8.x4.trans.shared.b16 {%0,%1,%2,%3}, [%4];"
                 : "=r"(v.x), "=r"(v.y), "=r"(v.z), "=r"(v.w) : "r"(a) : "memory");
    return v;
}
__device__ __forceinline__ void mma16816(float (&c)[4], uint32_t a0, uint32_t a1, uint32_t a2, uint32_t a3, uint32_t b0, uint32_t b1) {
    asm volatile("mma.sync.aligned.m16n8k16.row.col.f32.bf16.bf16.f32 {%0,%1,%2,%3}, {%4,%5,%6,%7}, {%8,%9}, {%0,%1,%2,%3};"
                 : "+f"(c[0]), "+f"(c[1]), "+f"(c[2]), "+f"(c[3])
                 : "r"(a0), "r"(a1), "r"(a2), "r"(a3), "r"(b0), "r"(b1));
}
__device__ __forceinline__ uint32_t pack_bf16(float lo, float hi) {
    uint32_t r;
    asm("cvt.rn.bf16x2.f32 %0, %1, %2;" : "=r"(r) : "f"(hi), "f"(lo));
    return r;
}
__device__ __forceinline__ float ex2(float x) { float y; asm("ex2.approx.ftz.f32 %0, %1;" : "=f"(y) : "f"(x)); return y; }
__device__ __forceinline__ float bf_lo(uint32_t u) { return __uint_as_float(u << 16); }
__device__ __forceinline__ float bf_hi(uint32_t u) { return __uint_as_float(u & 0xffff0000u); }

__device__ __forceinline__ uint32_t encw(uint32_t w) { return w ? w : 0x80000000u; }
__device__ __forceinline__ uint32_t enc(float f) { return encw(__float_as_uint(f)); }
__device__ __forceinline__ float dec(uint32_t u) { return __uint_as_float(u); }
__device__ __forceinline__ void st_rlx4v(uint32_t* p, uint4 v) { asm volatile("st.relaxed.gpu.global.v4.u32 [%0], {%1,%2,%3,%4};" ::"l"(p), "r"(v.x), "r"(v.y), "r"(v.z), "r"(v.w) : "memory"); }
__device__ __forceinline__ uint2 ld_rlx2(const uint32_t* p) { uint2 v; asm volatile("ld.relaxed.gpu.global.v2.u32 {%0,%1}, [%2];" : "=r"(v.x), "=r"(v.y) : "l"(p) : "memory"); return v; }
__device__ __forceinline__ void st_rlx2(uint32_t* p, uint32_t a, uint32_t b) { asm volatile("st.relaxed.gpu.global.v2.u32 [%0], {%1,%2};" ::"l"(p), "r"(a), "r"(b) : "memory"); }
__device__ __forceinline__ void st_rlx4(uint32_t* p, uint32_t a) { asm volatile("st.relaxed.gpu.global.v4.u32 [%0], {%1,%1,%1,%1};" ::"l"(p), "r"(a) : "memory"); }
__device__ __forceinline__ uint32_t ld_rlx(const uint32_t* p) { uint32_t v; asm volatile("ld.relaxed.gpu.global.u32 %0, [%1];" : "=r"(v) : "l"(p) : "memory"); return v; }
__device__ __forceinline__ uint4 ld_rlx4(const uint32_t* p) { uint4 v; asm volatile("ld.relaxed.gpu.global.v4.u32 {%0,%1,%2,%3}, [%4];" : "=r"(v.x), "=r"(v.y), "=r"(v.z), "=r"(v.w) : "l"(p) : "memory"); return v; }
__device__ __forceinline__ uint32_t min4(uint4 v) { return min(min(v.x, v.y), min(v.z, v.w)); }

constexpr float SCALE_LOG2E = 0.08838834764831845f * 1.4426950408889634f;

__device__ __forceinline__ void merge4(float& M, float& L, float4& o, float M2, float L2, float4 o2) {
    const float Mx = fmaxf(M, M2);
    const float f = ex2((M - Mx) * SCALE_LOG2E), f2 = ex2((M2 - Mx) * SCALE_LOG2E);
    M = Mx; L = f * L + f2 * L2;
    o.x = f * o.x + f2 * o2.x; o.y = f * o.y + f2 * o2.y; o.z = f * o.z + f2 * o2.z; o.w = f * o.w + f2 * o2.w;
}
__device__ __forceinline__ int phase_tiles(int ph) { return ph == 0 ? N0 : ph == NPH - 2 ? N1 : ph == NPH - 1 ? 8 - N0 - N1 : 4; }

__global__ void __cluster_dims__(NSPLIT, 1, 1) __launch_bounds__(NTHREADS, 1) gqa_decode_fused(const __grid_constant__ Params P) {
    extern __shared__ __align__(1024) unsigned char smem[];
    const int tid = threadIdx.x;
    const int cta = blockIdx.x;
    const int group = cta >> 1, s = cta & 1;
    const int br = group >> 4, h = group & 15;
    {
        const __nv_bfloat16* w = P.wq[br] + (size_t)(s * QROWS_PER_CTA + (tid >> 2)) * QCOLS + h * 256 + (tid & 3) * 64;
#pragma unroll
        for (int i = 0; i < PFN; i++)
            if (tid < 256) asm volatile("prefetch.global.L2 [%0];" ::"l"(w + (size_t)i * 64 * QCOLS));
    }
    const int warp = __shfl_sync(0xffffffffu, tid >> 5, 0), lane = tid & 31;

    uint32_t sb;
    asm volatile("mov.u32 %0, %1;" : "=r"(sb) : "r"(smem_u32(smem)));
    const int g = lane >> 2, t = lane & 3;
    const uint32_t bar_full = sb + SM_BAR, bar_empty = bar_full + NS * 8, bar_wq = bar_empty + NS * 8;
    const uint32_t bar_pq = bar_wq + 8 * 8, bar_po = bar_pq + 8;
    const uint32_t bar_qfull = bar_po + 8, bar_qfree = bar_qfull + 16, bar_redfree = bar_qfree + 16, bar_redfull = bar_redfree + 8, bar_gath = bar_redfull + 8;
    const int m = cta & (NSRC - 1);
    float* red = reinterpret_cast<float*>(smem + SM_RED);
    volatile uint32_t* ctl = reinterpret_cast<volatile uint32_t*>(smem + SM_CTL);
    uint32_t* const rbox = P.mail;
    unsigned long long* const cword = reinterpret_cast<unsigned long long*>(P.mail + CW_OFF);
    unsigned long long cold = 0;

    if (warp < 8) {
        const int grp = warp >> 2, w4 = warp & 3;
        const int row0 = s * QROWS_PER_CTA + grp * 36 + w4 * 9;
        const uint32_t wsm = sb + SM_RING + (WQ_SLOT0 + grp) * SLOT_BYTES + w4 * 9 * 512;
        const uint32_t wbar = bar_wq + grp * 8;
        const int xl = lane < 27 ? lane : 0;
        const float xv = __bfloat162float(P.x[br][row0 + 72 * (xl / 9) + xl % 9]);
        const float xw = __bfloat162float(P.x[br][row0 + 216 + (lane < 9 ? lane : 0)]);
        cluster_arrive();
        bar_sync(1, 288);
        float a[8];
#pragma unroll
        for (int j = 0; j < 8; j++) a[j] = 0.f;
#pragma unroll 1
        for (int j = 0; j < 4; j++) {
            mbar_wait(wbar + j * 16, 0);
            const float xs = j < 3 ? xv : xw;
            const int xb = j < 3 ? 9 * j : 0;
#pragma unroll
            for (int i = 0; i < 9; i++) {
                const uint4 w = lds128(wsm + j * 2 * SLOT_BYTES + i * 512 + lane * 16);
                const float xi = __shfl_sync(0xffffffffu, xs, xb + i);
                a[0] = fmaf(xi, bf_lo(w.x), a[0]); a[1] = fmaf(xi, bf_hi(w.x), a[1]);
                a[2] = fmaf(xi, bf_lo(w.y), a[2]); a[3] = fmaf(xi, bf_hi(w.y), a[3]);
                a[4] = fmaf(xi, bf_lo(w.z), a[4]); a[5] = fmaf(xi, bf_hi(w.z), a[5]);
                a[6] = fmaf(xi, bf_lo(w.w), a[6]); a[7] = fmaf(xi, bf_hi(w.w), a[7]);
            }
            __syncwarp();
            if (lane == 0) mbar_arrive(bar_empty + (WQ_SLOT0 + 2 * j + grp) * 8);
        }
        float4* dst = reinterpret_cast<float4*>(red + warp * 256 + lane * 8);
        dst[0] = make_float4(a[0], a[1], a[2], a[3]);
        dst[1] = make_float4(a[4], a[5], a[6], a[7]);
        cluster_wait();
        bar_sync(1, 256);
        uint32_t peer;
        asm volatile("mapa.shared::cluster.u32 %0, %1, %2;" : "=r"(peer) : "r"(sb), "r"(s ^ 1));
        {
            float part = 0.f;
#pragma unroll
            for (int w8 = 0; w8 < 8; w8++) part += red[w8 * 256 + tid];
            st_peer(peer + SM_PQ + tid * 4, part, peer + (bar_pq - sb));
            mbar_wait_cluster(bar_pq, 0);
            reinterpret_cast<__nv_bfloat16*>(smem + SM_Q)[tid] = __float2bfloat16(part + reinterpret_cast<const float*>(smem + SM_PQ)[tid]);
        }
        bar_sync(1, 256);

        if (lane == 0) { mbar_arrive(bar_qfree); mbar_arrive(bar_qfree + 8); }
        {
            const uint4 w0 = lds128(sb + SM_Q + (tid & 15) * 32), w1 = lds128(sb + SM_Q + (tid & 15) * 32 + 16);
            uint32_t* qd = P.mail + QB_OFF + ((br * NSRC + s * 16 + (tid >> 4)) * HKV + h) * 128 + (tid & 15) * 8;
            st_rlx4v(qd, make_uint4(encw(w0.x), encw(w0.y), encw(w0.z), encw(w0.w)));
            st_rlx4v(qd + 4, make_uint4(encw(w1.x), encw(w1.y), encw(w1.z), encw(w1.w)));
        }

        const uint32_t qoff = (g & 1) * 256 + (t << 4);
        const uint32_t koffA = (w4 * 16 + g) * 256 + t * 16 + (g & 1) * 64;
        const uint32_t koffB = (w4 * 16 + g) * 256 + t * 16 + ((g & 1) ^ 1) * 64;
        const int vi = lane & 7;
        const int vkey = 8 * (lane >> 4) + ((vi < 4) ? 2 * vi : 2 * (vi - 4) + 1);
        const uint32_t voff = (w4 * 16 + vkey) * 256 + ((((lane >> 3) & 1) ^ vi) << 4);
        const int kap = (g >> 1) | ((g & 1) << 2);
        const bool valid = (t >> 1) == (g & 1);
        const uint32_t amask = (t == (kap >> 1)) ? ((kap & 1) ? 0xffff0000u : 0x0000ffffu) : 0u;
        float* ml = reinterpret_cast<float*>(smem + SM_ML);
        int ib = 0;
#pragma unroll 1
        for (int ph = 0; ph < NPH; ph++) {
            const int n = phase_tiles(ph);
            const bool own = ph == 0 || ph > HKV;
            const bool two = grp + 2 < n;
            const bool use2 = two && (own || warp < 6);
            if (ph == NPH - 2 && tid == 0) ctl[17] = 1;
            uint32_t tb, fb;
            auto acquire = [&](int i) {
                const int q12 = (i * 171) >> 11, slot = i - q12 * NS;
                fb = bar_full + slot * 8; tb = sb + SM_RING + slot * SLOT_BYTES;
                mbar_wait(fb, q12 & 1);
            };
            auto release = [&]() { __syncwarp(); if (lane == 0) mbar_arrive(fb + NS * 8); };
            uint4 qf[4];
            {
                const int p = ph - 1;
                if (!own) mbar_wait(bar_qfull + (p & 1) * 8, (p >> 1) & 1);
                const uint32_t qb = sb + (own ? SM_Q : SM_PQ + (p & 1) * 512) + qoff;
#pragma unroll
                for (int j = 0; j < 4; j++) qf[j] = lds128(qb + ((j ^ (g >> 2)) << 6));
                __syncwarp();
                if (!own && lane == 0) mbar_arrive(bar_qfree + (p & 1) * 8);
            }
            float sv[2][4];
#pragma unroll
            for (int u = 0; u < 2; u++) {
                float sa[4] = {0.f, 0.f, 0.f, 0.f}, sc[4] = {0.f, 0.f, 0.f, 0.f};
                if (u == 0 || two) {
                    acquire(ib + grp + 2 * u);
                    if (u == 0 || use2) {
                        uint4 Lo[4], Hi[4];
                        Lo[0] = lds128(tb + koffA);       Hi[0] = lds128(tb + koffA + 2048);
                        Lo[1] = lds128(tb + koffB);       Hi[1] = lds128(tb + koffB + 2048);
                        Lo[2] = lds128(tb + koffA + 128); Hi[2] = lds128(tb + koffA + 128 + 2048);
                        Lo[3] = lds128(tb + koffB + 128); Hi[3] = lds128(tb + koffB + 128 + 2048);
#pragma unroll
                        for (int j = 0; j < 4; j++) {
                            mma16816(sa, Lo[j].x, Hi[j].x, Lo[j].y, Hi[j].y, qf[j].x, qf[j].y);
                            mma16816(sc, Lo[j].z, Hi[j].z, Lo[j].w, Hi[j].w, qf[j].z, qf[j].w);
                        }
                    }
                    release();
                }
#pragma unroll
                for (int e = 0; e < 4; e++) sv[u][e] = (valid && (u == 0 || use2)) ? sa[e] + sc[e] : -INFINITY;
            }
            float m0 = fmaxf(fmaxf(fmaxf(sv[0][0], sv[0][2]), fmaxf(sv[1][0], sv[1][2])), -3.0e38f);
            float m1 = fmaxf(fmaxf(fmaxf(sv[0][1], sv[0][3]), fmaxf(sv[1][1], sv[1][3])), -3.0e38f);
#pragma unroll
            for (int x = 2; x <= 16; x <<= 1) {
                m0 = fmaxf(m0, __shfl_xor_sync(0xffffffffu, m0, x));
                m1 = fmaxf(m1, __shfl_xor_sync(0xffffffffu, m1, x));
            }
            float l0 = 0.f, l1 = 0.f;
            uint32_t pb[2][4];
#pragma unroll
            for (int u = 0; u < 2; u++) {
                const float p0 = ex2((sv[u][0] - m0) * SCALE_LOG2E), p1 = ex2((sv[u][1] - m1) * SCALE_LOG2E);
                const float p2 = ex2((sv[u][2] - m0) * SCALE_LOG2E), p3 = ex2((sv[u][3] - m1) * SCALE_LOG2E);
                l0 += p0 + p2; l1 += p1 + p3;
                pb[u][0] = pack_bf16(p0, p0) & amask; pb[u][1] = pack_bf16(p1, p1) & amask;
                pb[u][2] = pack_bf16(p2, p2) & amask; pb[u][3] = pack_bf16(p3, p3) & amask;
            }
#pragma unroll
            for (int x = 2; x <= 16; x <<= 1) {
                l0 += __shfl_xor_sync(0xffffffffu, l0, x);
                l1 += __shfl_xor_sync(0xffffffffu, l1, x);
            }
            float acc[16][4];
#pragma unroll
            for (int i = 0; i < 16; i++) { acc[i][0] = acc[i][1] = acc[i][2] = acc[i][3] = 0.f; }
#pragma unroll
            for (int u = 0; u < 2; u++) {
                if (u == 0 || two) {
                    const int i = ib + n + grp + 2 * u;
                    acquire(i);
                    if ((tid & 127) == 0 && u + grp == 1 && ph >= 2 && ph <= CTL_LAST) {
                        const int e = max(min((int)(gtime32() - ctl[i & 15]) - LAT_TARGET, 2000), -1000);
                        asm volatile("red.relaxed.gpu.global.add.u64 [%0], %1;" ::"l"(cword), "l"((unsigned long long)(long long)e << 32) : "memory");
                    }
                    if (u == 0 || use2) {
#pragma unroll
                        for (int j = 0; j < 8; j++) {
                            const uint4 a = ldsm4t(tb + (voff ^ ((j & 3) << 5)) + (j >> 2) * 128);
                            mma16816(acc[j], a.x, a.y, a.z, a.w, pb[u][0], pb[u][2]);
                            mma16816(acc[8 + j], a.x, a.y, a.z, a.w, pb[u][1], pb[u][3]);
                        }
                    }
                    release();
                }
            }
            ib += 2 * n;
            if (ph > 0) mbar_wait(bar_redfree, (ph - 1) & 1);
#pragma unroll
            for (int q = 0; q < 4; q++) {
                float r[8];
#pragma unroll
                for (int y = 0; y < 8; y++) r[y] = acc[4 * q + (y >> 1)][2 * (y & 1)] + acc[4 * q + ((y ^ 4) >> 1)][2 * (y & 1) + 1];
#pragma unroll
                for (int y = 0; y < 8; y += 2) r[y] += __shfl_xor_sync(0xffffffffu, r[y + 1], 1);
                r[0] += __shfl_xor_sync(0xffffffffu, r[2], 2);
                r[4] += __shfl_xor_sync(0xffffffffu, r[6], 2);
                float* dst2 = red + warp * 256 + q * 64 + t * 8 + g;
                dst2[0] = r[0];
                dst2[32] = r[4];
            }
            if (lane == 0) *reinterpret_cast<float4*>(ml + warp * 4) = make_float4(m0, l0, m1, l1);
            __syncwarp();
            if (lane == 0) mbar_arrive(bar_redfull);
            if ((tid & 127) == 0 && ph == CTL_LAST)
                asm volatile("atom.relaxed.gpu.global.add.u64 %0, [%1], %2;" : "=l"(cold) : "l"(cword), "l"(1ull) : "memory");
        }
    } else if (warp == 8) {
        const uint32_t t_entry = gtime32();
        if (lane == 0) {
            asm volatile("prefetch.param.tensormap [%0];" ::"l"(__cvta_generic_to_grid_constant(&P.wq_map[br])) : "memory");
#pragma unroll
            for (int i = 0; i < 8; i++) mbar_init(bar_wq + i * 8, 1);
            asm volatile("fence.mbarrier_init.release.cluster;" ::: "memory");
        }
        __syncwarp();
        uint64_t pol;
        asm volatile("createpolicy.fractional.L2::evict_first.b64 %0, 1.0;" : "=l"(pol));
#pragma unroll
        for (int c = 0; c < 4; c++)
            expect_and_copy_2d(sb + SM_RING + (WQ_SLOT0 + c) * SLOT_BYTES, &P.wq_map[br], h * 256, s * QROWS_PER_CTA + c * 36, bar_wq + c * 8, pol);
        if (lane == 0) {
#pragma unroll
            for (int i = 0; i < 2 * NS; i++) mbar_init(bar_full + i * 8, i >= NS ? 4 : 1);
            mbar_init(bar_pq, 1);
            mbar_init(bar_po, 1);
            mbar_init(bar_qfull, 1); mbar_init(bar_qfull + 8, 1);
            mbar_init(bar_qfree, 8); mbar_init(bar_qfree + 8, 8);
            mbar_init(bar_redfree, 1); mbar_init(bar_redfull, 8); mbar_init(bar_gath, 1);
            asm volatile("fence.mbarrier_init.release.cluster;" ::: "memory");
            mbar_expect_tx(bar_pq, 256 * 4);
            mbar_expect_tx(bar_po, 130 * 4);
#pragma unroll
            for (int i = 0; i < WQ_SLOT0; i++) mbar_arrive_n(bar_empty + i * 8, 4);
            ctl[16] = 0; ctl[17] = 0;
        }
        __syncwarp();
        cluster_arrive();
        bar_arrive(1, 288);
        bar_arrive(3, 128);
#pragma unroll
        for (int c = 4; c < 8; c++)
            expect_and_copy_2d(sb + SM_RING + (WQ_SLOT0 + c) * SLOT_BYTES, &P.wq_map[br], h * 256, s * QROWS_PER_CTA + c * 36, bar_wq + c * 8, pol);
        const unsigned char* kp = reinterpret_cast<const unsigned char*>(P.k[br]);
        const unsigned char* vp = reinterpret_cast<const unsigned char*>(P.v[br]);
        const int own0 = h * 128 + OWN_TILE0 + s * 8;
        const unsigned char* wop = reinterpret_cast<const unsigned char*>(P.wo[br] + (size_t)(h * 256 + s * 128) * D_MODEL);
        if (lane == 0) {
            asm volatile("cp.async.bulk.prefetch.L2.global [%0], 16;" ::"l"(kp + (size_t)own0 * TILE_BYTES));
            asm volatile("cp.async.bulk.prefetch.L2.global [%0], 16;" ::"l"(vp + (size_t)own0 * TILE_BYTES));
            asm volatile("cp.async.bulk.prefetch.L2.global [%0], 16;" ::"l"(wop));
            asm volatile("cp.async.bulk.prefetch.L2.global [%0], 16;" ::"l"(wop + WO_CHUNKS * WO_CHUNK_BYTES - 16));
        }
        __syncwarp();
        if (lane < NPH) {
            const int nt = phase_tiles(lane);
            const int first = lane == 0 ? 0 : 2 * N0 + 8 * (lane - 1) - (lane == NPH - 1 ? 8 - 2 * N1 : 0);
            uint16_t* tab = reinterpret_cast<uint16_t*>(smem + SM_TAB) + first;
#pragma unroll
            for (int u = 0; u < 4; u++) {
                const int e = lane == 0 ? 2 * (own0 + u) : lane == NPH - 2 ? 2 * (own0 + N0 + u) : lane == NPH - 1 ? 2 * (own0 + N0 + N1 + u)
                            : (lane - 1) * 256 + (u < 3 ? 2 * (u * 32 + m) : (192 + m) | 0x4000);
                if (u < nt) { tab[u] = (uint16_t)e; tab[nt + u] = (uint16_t)(e | 0x8000); }
            }
        }
        __syncwarp();
        const uint32_t dt = P.dt, dte = dt + (dt >> 6) + (dt >> 7);
        uint32_t tnext = 2 * (t_entry + P.t0) + ((cta * dt) >> 6);
        uint32_t sbar = bar_full, sdst = sb + SM_RING, eph = 0;
        const uint32_t cs = sb + SM_CTL;
        auto issue = [&](int i, const unsigned char* src, uint32_t bytes) {
            mbar_wait(sbar + NS * 8, eph);
            unsigned n = 0;
            uint32_t now, shift;
#pragma unroll 1
            do {
                now = gtime32();
                asm volatile("ld.volatile.shared.u32 %0, [%1];" : "=r"(shift) : "r"(cs + 64) : "memory");
            } while ((int)(2 * (now - shift) - tnext) < 0 && ++n < SPIN_LIMIT);
            expect_and_copy(sdst, src, bytes, sbar, pol);
            asm volatile("st.volatile.shared.u32 [%0], %1;" ::"r"(cs + (i & 15) * 4), "r"(now) : "memory");
            sbar += 8; sdst += SLOT_BYTES;
            if (sbar == bar_empty) { sbar = bar_full; sdst = sb + SM_RING; eph ^= 1; }
        };
        uint32_t ent;
        asm volatile("ld.shared.u16 %0, [%1];" : "=r"(ent) : "r"(sb + SM_TAB) : "memory");
#pragma unroll 1
        for (int i = 0; i < NKV; i++) {
            const unsigned char* src = ((ent & 0x8000) ? vp : kp) + (size_t)((ent & 0x3fff) * (TILE_BYTES / 2));
            const uint32_t hs = (ent >> 14) & 1;
            asm volatile("ld.shared.u16 %0, [%1];" : "=r"(ent) : "r"(sb + SM_TAB + 2 * i + 2) : "memory");
            issue(i, src, TILE_BYTES >> hs);
            tnext += (i >= NKV - 2 * (8 - N0) ? dte : dt) >> hs;
        }
#pragma unroll 1
        for (int i = 0; i < WO_CHUNKS; i++) {
            issue(i, wop + i * WO_CHUNK_BYTES, WO_CHUNK_BYTES);
            tnext += dte + (dte >> 3);
        }
        cluster_wait();
    } else if (warp == 11) {
        cluster_arrive();
        bar_sync(3, 128);
        cluster_wait();
        const float* ml = reinterpret_cast<const float*>(smem + SM_ML);
        float Mk[2], Lk[2];
        float4 ok[2];
#pragma unroll 1
        for (int ph = 0; ph < NPH; ph++) {
            mbar_wait(bar_redfull, ph & 1);
            float M[2], L[2];
            float4 o[2];
            float4 w[8];
#pragma unroll
            for (int i = 0; i < 8; i++) w[i] = *reinterpret_cast<const float4*>(ml + i * 4);
            M[0] = w[0].x; M[1] = w[0].z;
#pragma unroll
            for (int i = 1; i < 8; i++) { M[0] = fmaxf(M[0], w[i].x); M[1] = fmaxf(M[1], w[i].z); }
#pragma unroll
            for (int hd = 0; hd < 2; hd++) {
                L[hd] = 0.f; o[hd] = make_float4(0.f, 0.f, 0.f, 0.f);
#pragma unroll
                for (int i = 0; i < 8; i++) {
                    const float f = ex2(((hd ? w[i].z : w[i].x) - M[hd]) * SCALE_LOG2E);
                    const float4 a = *reinterpret_cast<const float4*>(red + i * 256 + hd * 128 + lane * 4);
                    o[hd].x = fmaf(f, a.x, o[hd].x); o[hd].y = fmaf(f, a.y, o[hd].y);
                    o[hd].z = fmaf(f, a.z, o[hd].z); o[hd].w = fmaf(f, a.w, o[hd].w);
                    L[hd] = fmaf(f, hd ? w[i].w : w[i].y, L[hd]);
                }
            }
            __syncwarp();
            if (lane == 0) mbar_arrive(bar_redfree);
#pragma unroll
            for (int hd = 0; hd < 2; hd++) {
                if (ph == 0) {
                    Mk[hd] = M[hd]; Lk[hd] = L[hd]; ok[hd] = o[hd];
                } else if (ph > HKV) {
                    merge4(Mk[hd], Lk[hd], ok[hd], M[hd], L[hd], o[hd]);
                } else {
                    const int rec = (br * NSRC + (ph - 1) * 2 + hd) * NSRC + m;
                    st_rlx4v(P.mail + OB_OFF + rec * 128 + lane * 4, make_uint4(enc(o[hd].x), enc(o[hd].y), enc(o[hd].z), enc(o[hd].w)));
                    if (lane == 0) st_rlx2(P.mail + MB_OFF + rec * 2, enc(M[hd]), enc(L[hd]));
                }
            }
        }
        uint32_t peer;
        asm volatile("mapa.shared::cluster.u32 %0, %1, %2;" : "=r"(peer) : "r"(sb), "r"(s ^ 1));
        const float4 snd = s ? ok[0] : ok[1];
        asm volatile("st.async.shared::cluster.mbarrier::complete_tx::bytes.v4.f32 [%0], {%1,%2,%3,%4}, [%5];"
                     ::"r"(peer + SM_PO + lane * 16), "f"(snd.x), "f"(snd.y), "f"(snd.z), "f"(snd.w), "r"(peer + (bar_po - sb)) : "memory");
        if (lane < 2) st_peer(peer + SM_PO + 512 + lane * 4, lane ? (s ? Lk[0] : Lk[1]) : (s ? Mk[0] : Mk[1]), peer + (bar_po - sb));
        float Mg = s ? Mk[1] : Mk[0], Lg = s ? Lk[1] : Lk[0];
        float4 og = s ? ok[1] : ok[0];
        mbar_wait(bar_gath, 0);
        const float* gbuf = reinterpret_cast<const float*>(smem + SM_G);
        merge4(Mg, Lg, og, gbuf[128], gbuf[129], *reinterpret_cast<const float4*>(gbuf + lane * 4));
        mbar_wait_cluster(bar_po, 0);
        const float* pbuf = reinterpret_cast<const float*>(smem + SM_PO);
        merge4(Mg, Lg, og, pbuf[128], pbuf[129], *reinterpret_cast<const float4*>(pbuf + lane * 4));
        const float inv = __fdividef(1.0f, Lg);
        *reinterpret_cast<uint2*>(smem + SM_O + lane * 8) = make_uint2(pack_bf16(og.x * inv, og.y * inv), pack_bf16(og.z * inv, og.w * inv));
        bar_arrive(2, 320);
        return;
    } else {
        cluster_arrive();
        bar_sync(3, 128);
        cluster_wait();
        if (warp == 10) {
            uint32_t* qin = P.mail + QB_OFF + cta * HKV * 128 + lane * 4;
            uint4 cur = ld_rlx4(qin), nxt = ld_rlx4(qin + 128);
#pragma unroll 1
            for (int p = 0; p < HKV; p++) {
                mbar_wait(bar_qfree + (p & 1) * 8, (p >> 1) & 1);
                unsigned n = 0;
#pragma unroll 1
                while (min4(cur) == 0 && ++n < SPIN_LIMIT) cur = ld_rlx4(qin + p * 128);
                *reinterpret_cast<uint4*>(smem + SM_PQ + (p & 1) * 512 + lane * 16) = cur;
                __syncwarp();
                if (lane == 0) mbar_arrive(bar_qfull + (p & 1) * 8);
                st_rlx4(qin + p * 128, 0u);
                cur = nxt;
                nxt = make_uint4(0u, 0u, 0u, 0u);
            }
        }
        {
            uint32_t* mbox = P.mail + MB_OFF + (cta * NSRC + lane) * 2;
            bool pending = warp == 9;
            unsigned n = 0;
#pragma unroll 1
            while (++n < SPIN_LIMIT) {
                const bool run = __shfl_sync(0xffffffffu, ctl[17], 0) == 0;
                if (!run && !pending) break;
                if (run) __nanosleep(CTL_NAP);
                if (warp != 9) continue;
                uint2 y = make_uint2(0u, 0u);
                if (pending) y = ld_rlx2(mbox);
                if (run) {
                    const int sum = (int)ld_rlx(reinterpret_cast<const uint32_t*>(cword) + 1);
                    if (lane == 0) ctl[16] = (uint32_t)max(min(((sum >> 6) * CTL_GAIN) >> 8, 20000), -20000);
                }
                if (__all_sync(0xffffffffu, min(y.x, y.y) != 0)) {
                    pending = false;
                    uint32_t* box = P.mail + OB_OFF + cta * NSRC * 128 + lane * 4;
                    uint4 v[NSRC];
                    uint32_t z;
                    unsigned n2 = 0;
#pragma unroll 1
                    do {
#pragma unroll
                        for (int i = 0; i < NSRC; i++) v[i] = ld_rlx4(box + i * 128);
                        z = 0xffffffffu;
#pragma unroll
                        for (int i = 0; i < NSRC; i++) z = min(z, min4(v[i]));
                    } while (z == 0 && ++n2 < SPIN_LIMIT);
                    __syncwarp();
                    float Mg = dec(y.x);
#pragma unroll
                    for (int x = 1; x <= 16; x <<= 1) Mg = fmaxf(Mg, __shfl_xor_sync(0xffffffffu, Mg, x));
                    const float f = ex2((dec(y.x) - Mg) * SCALE_LOG2E);
                    float Lg = f * dec(y.y);
#pragma unroll
                    for (int x = 1; x <= 16; x <<= 1) Lg += __shfl_xor_sync(0xffffffffu, Lg, x);
                    float4 og = make_float4(0.f, 0.f, 0.f, 0.f);
#pragma unroll
                    for (int i = 0; i < NSRC; i++) {
                        const float fi = __shfl_sync(0xffffffffu, f, i);
                        og.x = fmaf(fi, dec(v[i].x), og.x); og.y = fmaf(fi, dec(v[i].y), og.y);
                        og.z = fmaf(fi, dec(v[i].z), og.z); og.w = fmaf(fi, dec(v[i].w), og.w);
                    }
                    float* gbuf = reinterpret_cast<float*>(smem + SM_G);
                    *reinterpret_cast<float4*>(gbuf + lane * 4) = og;
                    if (lane == 0) { gbuf[128] = Mg; gbuf[129] = Lg; }
                    __syncwarp();
                    if (lane == 0) mbar_arrive(bar_gath);
#pragma unroll 4
                    for (int i = 0; i < NSRC; i++) st_rlx4(box + i * 128, 0u);
                    st_rlx2(mbox, 0u, 0u);
                }
            }
        }
        const int ridx = 2 * m + (warp - 9);
        if (ridx < NRED) {
            uint32_t* rin = rbox + ((br * NRED + ridx) * NSRC + (lane >> 2)) * 16 + (lane & 3) * 4;
            uint32_t* outp = reinterpret_cast<uint32_t*>(P.out + br * D_MODEL + ridx * 16) + (lane & 7);
            const bool hi = lane & 4;
            uint4 r[4];
            unsigned n = 0;
            float a0, a1, a2, a3;
            auto take = [&](const uint4 (&v)[4]) {
                a0 = (dec(v[0].x) + dec(v[1].x)) + (dec(v[2].x) + dec(v[3].x));
                a1 = (dec(v[0].y) + dec(v[1].y)) + (dec(v[2].y) + dec(v[3].y));
                a2 = (dec(v[0].z) + dec(v[1].z)) + (dec(v[2].z) + dec(v[3].z));
                a3 = (dec(v[0].w) + dec(v[1].w)) + (dec(v[2].w) + dec(v[3].w));
                return __all_sync(0xffffffffu, min(min(min4(v[0]), min4(v[1])), min(min4(v[2]), min4(v[3]))) != 0);
            };
#pragma unroll 1
            do {
#pragma unroll
                for (int i = 0; i < 4; i++) r[i] = ld_rlx4(rin + i * 128);
            } while (!take(r) && ++n < SPIN_LIMIT);
            float lo = (hi ? a1 : a0) + __shfl_xor_sync(0xffffffffu, hi ? a0 : a1, 4);
            float up = (hi ? a3 : a2) + __shfl_xor_sync(0xffffffffu, hi ? a2 : a3, 4);
            lo += __shfl_xor_sync(0xffffffffu, lo, 8);  up += __shfl_xor_sync(0xffffffffu, up, 8);
            lo += __shfl_xor_sync(0xffffffffu, lo, 16); up += __shfl_xor_sync(0xffffffffu, up, 16);
            if (lane < 8) asm volatile("st.global.u32 [%0], %1;" ::"l"(outp), "r"(pack_bf16(lo, up)) : "memory");
#pragma unroll
            for (int i = 0; i < 4; i++) st_rlx4(rin + i * 128, 0u);
        }
        return;
    }

    {
        const int i8 = lane & 7;
        const uint32_t woff = sb + SM_RING + (8 * (lane >> 4) + i8) * WO_ROW_BYTES + warp * 128 + ((((lane >> 3) & 1) ^ i8) << 4);
        const uint32_t omask = (t == (g >> 1)) ? ((g & 1) ? 0xffff0000u : 0x0000ffffu) : 0u;
        uint32_t* rout = rbox + ((br * NRED + 4 * warp + t) * NSRC + m) * 16 + 2 * g;
        float c[4][4], c2[4][4];
#pragma unroll
        for (int i = 0; i < 4; i++) { c[i][0] = c[i][1] = c[i][2] = c[i][3] = 0.f; c2[i][0] = c2[i][1] = c2[i][2] = c2[i][3] = 0.f; }
        bar_sync(2, 320);
        const uint32_t* o32 = reinterpret_cast<const uint32_t*>(smem + SM_O);
        uint32_t ob[2 * WO_CHUNKS];
#pragma unroll
        for (int j = 0; j < 2 * WO_CHUNKS; j++) ob[j] = o32[4 * j + t] & omask;
#pragma unroll
        for (int ks = 0; ks < WO_CHUNKS - 2; ks += 2) {
            mbar_wait(bar_full + ((NKV + ks) % NS) * 8, ((NKV + ks) / NS) & 1);
            mbar_wait(bar_full + ((NKV + ks + 1) % NS) * 8, ((NKV + ks + 1) / NS) & 1);
            uint4 a[8];
#pragma unroll
            for (int j = 0; j < 8; j++) a[j] = ldsm4t((woff ^ ((j & 3) << 5)) + ((NKV + ks + (j >> 2)) % NS) * SLOT_BYTES);
#pragma unroll
            for (int j = 0; j < 4; j++) {
                mma16816(c[j], a[j].x, a[j].y, a[j].z, a[j].w, ob[2 * ks], ob[2 * ks + 1]);
                mma16816(c2[j], a[4 + j].x, a[4 + j].y, a[4 + j].z, a[4 + j].w, ob[2 * ks + 2], ob[2 * ks + 3]);
            }
        }
#pragma unroll
        for (int ks = WO_CHUNKS - 2; ks < WO_CHUNKS; ks++) {
            mbar_wait(bar_full + ((NKV + ks) % NS) * 8, ((NKV + ks) / NS) & 1);
#pragma unroll
            for (int j = 0; j < 4; j++) {
                const uint4 a = ldsm4t((woff ^ (j << 5)) + ((NKV + ks) % NS) * SLOT_BYTES);
                if (ks & 1) mma16816(c[j], a.x, a.y, a.z, a.w, ob[2 * ks], ob[2 * ks + 1]);
                else mma16816(c2[j], a.x, a.y, a.z, a.w, ob[2 * ks], ob[2 * ks + 1]);
            }
            if (ks == WO_CHUNKS - 2) {
#pragma unroll
                for (int j = 0; j < 4; j++) { c[j][0] += c2[j][0]; c[j][1] += c2[j][1]; c[j][2] += c2[j][2]; c[j][3] += c2[j][3]; }
            }
        }
        float r[8];
#pragma unroll
        for (int y = 0; y < 8; y++) r[y] = c[y >> 1][2 * (y & 1)] + c[y >> 1][2 * ((y ^ 1) & 1) + 1];
        r[0] += __shfl_xor_sync(0xffffffffu, r[2], 1);
        r[1] += __shfl_xor_sync(0xffffffffu, r[3], 1);
        r[4] += __shfl_xor_sync(0xffffffffu, r[6], 1);
        r[5] += __shfl_xor_sync(0xffffffffu, r[7], 1);
        r[0] += __shfl_xor_sync(0xffffffffu, r[4], 2);
        r[1] += __shfl_xor_sync(0xffffffffu, r[5], 2);
        st_rlx2(rout, enc(r[0]), enc(r[1]));
        if ((uint32_t)cold == 2 * NCTA - 1)
            asm volatile("st.relaxed.gpu.global.u64 [%0], %1;" ::"l"(cword), "l"(0ull) : "memory");
    }
}

}

extern "C" void kernel_launch(void* const* d_in, const int* in_sizes, int n_in, void* d_out, int out_size) {
    (void)in_sizes; (void)n_in; (void)out_size;
    typedef CUresult (*EncodeFn)(CUtensorMap*, CUtensorMapDataType, cuuint32_t, void*, const cuuint64_t*, const cuuint64_t*,
                                 const cuuint32_t*, const cuuint32_t*, CUtensorMapInterleave, CUtensorMapSwizzle,
                                 CUtensorMapL2promotion, CUtensorMapFloatOOBfill);
    static EncodeFn encode = nullptr;
    static uint32_t* mail = nullptr;
    static int dt = 650;
    if (!mail) {
        cudaFuncSetAttribute(gqa_decode_fused, cudaFuncAttributeMaxDynamicSharedMemorySize, SM_TOTAL);
        void* p = nullptr;
        cudaGetSymbolAddress(&p, g_mail);
        mail = (uint32_t*)p;
        cudaDriverEntryPointQueryResult qres = cudaDriverEntryPointSymbolNotFound;
        cudaGetDriverEntryPoint("cuTensorMapEncodeTiled", &p, cudaEnableDefault, &qres);
        encode = (qres == cudaDriverEntryPointSuccess) ? (EncodeFn)p : nullptr;
        int dev = 0, khz = 0, bits = 0;
        cudaGetDevice(&dev);
        if (cudaDeviceGetAttribute(&khz, cudaDevAttrMemoryClockRate, dev) == cudaSuccess &&
            cudaDeviceGetAttribute(&bits, cudaDevAttrGlobalMemoryBusWidth, dev) == cudaSuccess && khz > 0 && bits > 0) {
            const double bytes_per_ns = 2.0 * khz * 1e-6 * bits / 8.0;
            dt = (int)(2.0 * NCTA * TILE_BYTES / (0.9625 * bytes_per_ns) + 0.5);
        }
        (void)cudaGetLastError();
    }
    if (!encode) return;
    Params p;
    for (int b = 0; b < 2; b++) {
        p.x[b] = (const __nv_bfloat16*)d_in[5 * b + 0];
        p.k[b] = (const __nv_bfloat16*)d_in[5 * b + 1];
        p.v[b] = (const __nv_bfloat16*)d_in[5 * b + 2];
        p.wq[b] = (const __nv_bfloat16*)d_in[5 * b + 3];
        p.wo[b] = (const __nv_bfloat16*)d_in[5 * b + 4];
        const cuuint64_t dims[2] = {(cuuint64_t)QCOLS, (cuuint64_t)D_MODEL};
        const cuuint64_t strides[1] = {(cuuint64_t)QCOLS * 2};
        const cuuint32_t box[2] = {256, 36}, estr[2] = {1, 1};
        encode(&p.wq_map[b], CU_TENSOR_MAP_DATA_TYPE_BFLOAT16, 2, d_in[5 * b + 3], dims, strides, box, estr,
               CU_TENSOR_MAP_INTERLEAVE_NONE, CU_TENSOR_MAP_SWIZZLE_NONE, CU_TENSOR_MAP_L2_PROMOTION_NONE,
               CU_TENSOR_MAP_FLOAT_OOB_FILL_NONE);
    }
    p.out = (__nv_bfloat16*)d_out;
    p.mail = mail;
    p.dt = dt;
    p.t0 = dt * 9 / 2 > T0_LEAD ? dt * 9 / 2 - T0_LEAD : 0;
    gqa_decode_fused<<<NCTA, NTHREADS, SM_TOTAL>>>(p);
}
```

```cpp
#include <cuda.h>
#include <cuda_runtime.h>
#include <cuda_bf16.h>
#include <stdint.h>

namespace {

constexpr int D_MODEL = 576;
constexpr int HKV = 16;
constexpr int SK = 8192;
constexpr int DH = 128;
constexpr int QCOLS = 4096;
constexpr int NSPLIT = 2;
constexpr int NCTA = 2 * HKV * NSPLIT;
constexpr int TILE_KEYS = 64;
constexpr int TILE_BYTES = TILE_KEYS * DH * 2;
constexpr int NKV = 2 * (8 + HKV * 4);
constexpr int N0 = 2, N1 = 2;
constexpr int NPH = HKV + 3;
constexpr int OWN_TILE0 = 112;
static_assert(SK / TILE_KEYS == 128, "the phase schedule is written for this shape");
constexpr int NS = 12;
constexpr int WO_ROW_BYTES = D_MODEL * 2;
constexpr int WO_CHUNK_BYTES = 16 * WO_ROW_BYTES;
constexpr int WO_CHUNKS = 8;
constexpr int SLOT_BYTES = WO_CHUNK_BYTES;
constexpr int WQ_SLOT0 = NS - 8;
constexpr int QROWS_PER_CTA = D_MODEL / NSPLIT;
constexpr int NTHREADS = 384;
constexpr int NRED = 36;
constexpr int NSRC = HKV * NSPLIT;
constexpr unsigned SPIN_LIMIT = 1u << 19;

constexpr int LAT_TARGET = 1650;
constexpr int CTL_GAIN = 36;
constexpr int CTL_LAST = NPH - 3;
constexpr int CTL_NAP = 800;
constexpr int T0_LEAD = 875;
constexpr int PFN = 2;

constexpr int SM_RING = 0;
constexpr int SM_RED = SM_RING + NS * SLOT_BYTES;
constexpr int SM_PQ = SM_RED + 8 * 256 * 4;
constexpr int SM_PO = SM_PQ + 1024;
constexpr int SM_ML = SM_PO + 528;
constexpr int SM_Q = SM_ML + 128;
constexpr int SM_O = SM_Q;
constexpr int SM_BAR = SM_Q + 512;
constexpr int SM_G = SM_RING + (NS - 1) * SLOT_BYTES + TILE_BYTES;
constexpr int SM_TAB = SM_BAR + (2 * NS + 17) * 8;
constexpr int SM_CTL = SM_TAB + 296;
static_assert(NKV % NS + WO_CHUNKS < NS, "wo must not use the last slot");
constexpr int SM_TOTAL = SM_CTL + 80;
static_assert(SM_TOTAL <= 232448, "shared memory");

constexpr int RBOX_WORDS = 2 * NRED * NSRC * 16;
constexpr int QBOX_WORDS = NCTA * HKV * 128;
constexpr int OBOX_WORDS = NCTA * NSRC * 128;
constexpr int MBOX_WORDS = NCTA * NSRC * 2;
constexpr int CW_OFF = RBOX_WORDS, MB_OFF = CW_OFF + 32, QB_OFF = MB_OFF + MBOX_WORDS, OB_OFF = QB_OFF + QBOX_WORDS;
__device__ __align__(1024) uint32_t g_mail[OB_OFF + OBOX_WORDS];

struct Params {
    const __nv_bfloat16* wq[2];
    const __nv_bfloat16* x[2];
    const __nv_bfloat16* k[2];
    const __nv_bfloat16* v[2];
    const __nv_bfloat16* wo[2];
    __nv_bfloat16* out;
    uint32_t* mail;
    int dt, t0;
    CUtensorMap wq_map[2];
};

__device__ __forceinline__ uint32_t gtime32() { uint32_t t; asm volatile("mov.u32 %0, %globaltimer_lo;" : "=r"(t)); return t; }
__device__ __forceinline__ uint32_t smem_u32(const void* p) { return (uint32_t)__cvta_generic_to_shared(p); }
__device__ __forceinline__ void mbar_init(uint32_t bar, uint32_t cnt) {
    asm volatile("mbarrier.init.shared::cta.b64 [%0], %1;" ::"r"(bar), "r"(cnt) : "memory");
}
__device__ __forceinline__ void mbar_expect_tx(uint32_t bar, uint32_t bytes) {
    asm volatile("mbarrier.arrive.expect_tx.shared::cta.b64 _, [%0], %1;" ::"r"(bar), "r"(bytes) : "memory");
}
__device__ __forceinline__ void mbar_arrive(uint32_t bar) {
    asm volatile("mbarrier.arrive.shared::cta.b64 _, [%0];" ::"r"(bar) : "memory");
}
__device__ __forceinline__ void mbar_arrive_n(uint32_t bar, uint32_t n) {
    asm volatile("mbarrier.arrive.shared::cta.b64 _, [%0], %1;" ::"r"(bar), "r"(n) : "memory");
}
__device__ __forceinline__ void mbar_wait(uint32_t bar, uint32_t parity) {
    unsigned n = 0;
    uint32_t ok;
#pragma unroll 1
    do {
        asm volatile("{\n.reg .pred p;\nmbarrier.try_wait.parity.shared::cta.b64 p, [%1], %2;\nselp.u32 %0, 1, 0, p;\n}"
                     : "=r"(ok) : "r"(bar), "r"(parity) : "memory");
    } while (!ok && ++n <= SPIN_LIMIT);
}
__device__ __forceinline__ void mbar_wait_cluster(uint32_t bar, uint32_t parity) {
    unsigned n = 0;
    uint32_t ok;
#pragma unroll 1
    do {
        asm volatile("{\n.reg .pred p;\nmbarrier.try_wait.parity.acquire.cluster.shared::cta.b64 p, [%1], %2;\nselp.u32 %0, 1, 0, p;\n}"
                     : "=r"(ok) : "r"(bar), "r"(parity) : "memory");
    } while (!ok && ++n <= SPIN_LIMIT);
}
__device__ __forceinline__ void expect_and_copy(uint32_t dst, const void* src, uint32_t bytes, uint32_t bar, uint64_t pol) {
    asm volatile("{\n.reg .pred p;\nelect.sync _|p, 0xffffffff;\n"
                 "@p mbarrier.arrive.expect_tx.shared::cta.b64 _, [%3], %2;\n"
                 "@p cp.async.bulk.shared::cluster.global.mbarrier::complete_tx::bytes.L2::cache_hint [%0], [%1], %2, [%3], %4;\n}"
                 ::"r"(dst), "l"(src), "r"(bytes), "r"(bar), "l"(pol) : "memory");
}
__device__ __forceinline__ void expect_and_copy_2d(uint32_t dst, const CUtensorMap* map, int c0, int c1, uint32_t bar, uint64_t pol) {
    asm volatile("{\n.reg .pred p;\nelect.sync _|p, 0xffffffff;\n"
                 "@p mbarrier.arrive.expect_tx.shared::cta.b64 _, [%2], %6;\n"
                 "@p cp.async.bulk.tensor.2d.shared::cluster.global.mbarrier::complete_tx::bytes.L2::cache_hint [%0], [%1, {%3, %4}], [%2], %5;\n}"
                 ::"r"(dst), "l"(map), "r"(bar), "r"(c0), "r"(c1), "l"(pol), "n"(SLOT_BYTES) : "memory");
}
__device__ __forceinline__ void st_peer(uint32_t peer_addr, float v, uint32_t peer_bar) {
    asm volatile("st.async.shared::cluster.mbarrier::complete_tx::bytes.f32 [%0], %1, [%2];" ::"r"(peer_addr), "f"(v), "r"(peer_bar) : "memory");
}
__device__ __forceinline__ void bar_sync(int id, int n) { asm volatile("bar.sync %0, %1;" ::"r"(id), "r"(n) : "memory"); }
__device__ __forceinline__ void bar_arrive(int id, int n) { asm volatile("bar.arrive %0, %1;" ::"r"(id), "r"(n) : "memory"); }
__device__ __forceinline__ void cluster_arrive() { asm volatile("barrier.cluster.arrive.relaxed.aligned;" ::: "memory"); }
__device__ __forceinline__ void cluster_wait() { asm volatile("barrier.cluster.wait.acquire.aligned;" ::: "memory"); }

__device__ __forceinline__ uint4 lds128(uint32_t a) {
    uint4 v;
    asm volatile("ld.shared.v4.u32 {%0,%1,%2,%3}, [%4];" : "=r"(v.x), "=r"(v.y), "=r"(v.z), "=r"(v.w) : "r"(a) : "memory");
    return v;
}
__device__ __forceinline__ uint4 ldsm4t(uint32_t a) {
    uint4 v;
    asm volatile("ldmatrix.sync.aligned.m8n8.x4.trans.shared.b16 {%0,%1,%2,%3}, [%4];"
                 : "=r"(v.x), "=r"(v.y), "=r"(v.z), "=r"(v.w) : "r"(a) : "memory");
    return v;
}
__device__ __forceinline__ void mma16816(float (&c)[4], uint32_t a0, uint32_t a1, uint32_t a2, uint32_t a3, uint32_t b0, uint32_t b1) {
    asm volatile("mma.sync.aligned.m16n8k16.row.col.f32.bf16.bf16.f32 {%0,%1,%2,%3}, {%4,%5,%6,%7}, {%8,%9}, {%0,%1,%2,%3};"
                 : "+f"(c[0]), "+f"(c[1]), "+f"(c[2]), "+f"(c[3])
                 : "r"(a0), "r"(a1), "r"(a2), "r"(a3), "r"(b0), "r"(b1));
}
__device__ __forceinline__ uint32_t pack_bf16(float lo, float hi) {
    uint32_t r;
    asm("cvt.rn.bf16x2.f32 %0, %1, %2;" : "=r"(r) : "f"(hi), "f"(lo));
    return r;
}
__device__ __forceinline__ float ex2(float x) { float y; asm("ex2.approx.ftz.f32 %0, %1;" : "=f"(y) : "f"(x)); return y; }
__device__ __forceinline__ float bf_lo(uint32_t u) { return __uint_as_float(u << 16); }
__device__ __forceinline__ float bf_hi(uint32_t u) { return __uint_as_float(u & 0xffff0000u); }

__device__ __forceinline__ uint32_t encw(uint32_t w) { return w ? w : 0x80000000u; }
__device__ __forceinline__ uint32_t enc(float f) { return encw(__float_as_uint(f)); }
__device__ __forceinline__ float dec(uint32_t u) { return __uint_as_float(u); }
__device__ __forceinline__ void st_rlx4v(uint32_t* p, uint4 v) { asm volatile("st.relaxed.gpu.global.v4.u32 [%0], {%1,%2,%3,%4};" ::"l"(p), "r"(v.x), "r"(v.y), "r"(v.z), "r"(v.w) : "memory"); }
__device__ __forceinline__ uint2 ld_rlx2(const uint32_t* p) { uint2 v; asm volatile("ld.relaxed.gpu.global.v2.u32 {%0,%1}, [%2];" : "=r"(v.x), "=r"(v.y) : "l"(p) : "memory"); return v; }
__device__ __forceinline__ void st_rlx2(uint32_t* p, uint32_t a, uint32_t b) { asm volatile("st.relaxed.gpu.global.v2.u32 [%0], {%1,%2};" ::"l"(p), "r"(a), "r"(b) : "memory"); }
__device__ __forceinline__ void st_rlx4(uint32_t* p, uint32_t a) { asm volatile("st.relaxed.gpu.global.v4.u32 [%0], {%1,%1,%1,%1};" ::"l"(p), "r"(a) : "memory"); }
__device__ __forceinline__ uint32_t ld_rlx(const uint32_t* p) { uint32_t v; asm volatile("ld.relaxed.gpu.global.u32 %0, [%1];" : "=r"(v) : "l"(p) : "memory"); return v; }
__device__ __forceinline__ uint4 ld_rlx4(const uint32_t* p) { uint4 v; asm volatile("ld.relaxed.gpu.global.v4.u32 {%0,%1,%2,%3}, [%4];" : "=r"(v.x), "=r"(v.y), "=r"(v.z), "=r"(v.w) : "l"(p) : "memory"); return v; }
__device__ __forceinline__ uint32_t min4(uint4 v) { return min(min(v.x, v.y), min(v.z, v.w)); }

constexpr float SCALE_LOG2E = 0.08838834764831845f * 1.4426950408889634f;

__device__ __forceinline__ void merge4(float& M, float& L, float4& o, float M2, float L2, float4 o2) {
    const float Mx = fmaxf(M, M2);
    const float f = ex2((M - Mx) * SCALE_LOG2E), f2 = ex2((M2 - Mx) * SCALE_LOG2E);
    M = Mx; L = f * L + f2 * L2;
    o.x = f * o.x + f2 * o2.x; o.y = f * o.y + f2 * o2.y; o.z = f * o.z + f2 * o2.z; o.w = f * o.w + f2 * o2.w;
}
__device__ __forceinline__ int phase_tiles(int ph) { return ph == 0 ? N0 : ph == NPH - 2 ? N1 : ph == NPH - 1 ? 8 - N0 - N1 : 4; }

__global__ void __cluster_dims__(NSPLIT, 1, 1) __launch_bounds__(NTHREADS, 1) gqa_decode_fused(const __grid_constant__ Params P) {
    extern __shared__ __align__(1024) unsigned char smem[];
    const int tid = threadIdx.x;
    const int cta = blockIdx.x;
    const int group = cta >> 1, s = cta & 1;
    const int br = group >> 4, h = group & 15;
    {
        const __nv_bfloat16* w = P.wq[br] + (size_t)(s * QROWS_PER_CTA + (tid >> 2)) * QCOLS + h * 256 + (tid & 3) * 64;
#pragma unroll
        for (int i = 0; i < PFN; i++)
            if (tid < 256) asm volatile("prefetch.global.L2 [%0];" ::"l"(w + (size_t)i * 64 * QCOLS));
    }
    const int warp = __shfl_sync(0xffffffffu, tid >> 5, 0), lane = tid & 31;

    uint32_t sb;
    asm volatile("mov.u32 %0, %1;" : "=r"(sb) : "r"(smem_u32(smem)));
    const int g = lane >> 2, t = lane & 3;
    const uint32_t bar_full = sb + SM_BAR, bar_empty = bar_full + NS * 8, bar_wq = bar_empty + NS * 8;
    const uint32_t bar_pq = bar_wq + 8 * 8, bar_po = bar_pq + 8;
    const uint32_t bar_qfull = bar_po + 8, bar_qfree = bar_qfull + 16, bar_redfree = bar_qfree + 16, bar_redfull = bar_redfree + 8, bar_gath = bar_redfull + 8;
    const int m = cta & (NSRC - 1);
    float* red = reinterpret_cast<float*>(smem + SM_RED);
    volatile uint32_t* ctl = reinterpret_cast<volatile uint32_t*>(smem + SM_CTL);
    uint32_t* const rbox = P.mail;
    unsigned long long* const cword = reinterpret_cast<unsigned long long*>(P.mail + CW_OFF);
    unsigned long long cold = 0;

    if (warp < 8) {
        const int grp = warp >> 2, w4 = warp & 3;
        const int row0 = s * QROWS_PER_CTA + grp * 36 + w4 * 9;
        const uint32_t wsm = sb + SM_RING + (WQ_SLOT0 + grp) * SLOT_BYTES + w4 * 9 * 512;
        const uint32_t wbar = bar_wq + grp * 8;
        const int xl = lane < 27 ? lane : 0;
        const float xv = __bfloat162float(P.x[br][row0 + 72 * (xl / 9) + xl % 9]);
        const float xw = __bfloat162float(P.x[br][row0 + 216 + (lane < 9 ? lane : 0)]);
        cluster_arrive();
        bar_sync(1, 288);
        float a[8];
#pragma unroll
        for (int j = 0; j < 8; j++) a[j] = 0.f;
#pragma unroll 1
        for (int j = 0; j < 4; j++) {
            mbar_wait(wbar + j * 16, 0);
            const float xs = j < 3 ? xv : xw;
            const int xb = j < 3 ? 9 * j : 0;
#pragma unroll
            for (int i = 0; i < 9; i++) {
                const uint4 w = lds128(wsm + j * 2 * SLOT_BYTES + i * 512 + lane * 16);
                const float xi = __shfl_sync(0xffffffffu, xs, xb + i);
                a[0] = fmaf(xi, bf_lo(w.x), a[0]); a[1] = fmaf(xi, bf_hi(w.x), a[1]);
                a[2] = fmaf(xi, bf_lo(w.y), a[2]); a[3] = fmaf(xi, bf_hi(w.y), a[3]);
                a[4] = fmaf(xi, bf_lo(w.z), a[4]); a[5] = fmaf(xi, bf_hi(w.z), a[5]);
                a[6] = fmaf(xi, bf_lo(w.w), a[6]); a[7] = fmaf(xi, bf_hi(w.w), a[7]);
            }
            __syncwarp();
            if (lane == 0) mbar_arrive(bar_empty + (WQ_SLOT0 + 2 * j + grp) * 8);
        }
        float4* dst = reinterpret_cast<float4*>(red + warp * 256 + lane * 8);
        dst[0] = make_float4(a[0], a[1], a[2], a[3]);
        dst[1] = make_float4(a[4], a[5], a[6], a[7]);
        cluster_wait();
        bar_sync(1, 256);
        uint32_t peer;
        asm volatile("mapa.shared::cluster.u32 %0, %1, %2;" : "=r"(peer) : "r"(sb), "r"(s ^ 1));
        {
            float part = 0.f;
#pragma unroll
            for (int w8 = 0; w8 < 8; w8++) part += red[w8 * 256 + tid];
            st_peer(peer + SM_PQ + tid * 4, part, peer + (bar_pq - sb));
            mbar_wait_cluster(bar_pq, 0);
            reinterpret_cast<__nv_bfloat16*>(smem + SM_Q)[tid] = __float2bfloat16(part + reinterpret_cast<const float*>(smem + SM_PQ)[tid]);
        }
        bar_sync(1, 256);

        if (lane == 0) { mbar_arrive(bar_qfree); mbar_arrive(bar_qfree + 8); }
        {
            const uint4 w = lds128(sb + SM_Q + lane * 16);
            const uint4 e = make_uint4(encw(w.x), encw(w.y), encw(w.z), encw(w.w));
            uint32_t* qd = P.mail + QB_OFF + ((br * NSRC + s * 16 + warp * 2) * HKV + h) * 128 + lane * 4;
            st_rlx4v(qd, e);
            st_rlx4v(qd + HKV * 128, e);
        }

        const uint32_t qoff = (g & 1) * 256 + (t << 4);
        const uint32_t koffA = (w4 * 16 + g) * 256 + t * 16 + (g & 1) * 64;
        const uint32_t koffB = (w4 * 16 + g) * 256 + t * 16 + ((g & 1) ^ 1) * 64;
        const int vi = lane & 7;
        const int vkey = 8 * (lane >> 4) + ((vi < 4) ? 2 * vi : 2 * (vi - 4) + 1);
        const uint32_t voff = (w4 * 16 + vkey) * 256 + ((((lane >> 3) & 1) ^ vi) << 4);
        const int kap = (g >> 1) | ((g & 1) << 2);
        const bool valid = (t >> 1) == (g & 1);
        const uint32_t amask = (t == (kap >> 1)) ? ((kap & 1) ? 0xffff0000u : 0x0000ffffu) : 0u;
        float* ml = reinterpret_cast<float*>(smem + SM_ML);
        int ib = 0;
#pragma unroll 1
        for (int ph = 0; ph < NPH; ph++) {
            const int n = phase_tiles(ph);
            const bool own = ph == 0 || ph > HKV;
            const bool two = grp + 2 < n;
            const bool use2 = two && (own || warp < 6);
            if (ph == NPH - 2 && tid == 0) ctl[17] = 1;
            uint32_t tb, fb;
            auto acquire = [&](int i) {
                const int q12 = (i * 171) >> 11, slot = i - q12 * NS;
                fb = bar_full + slot * 8; tb = sb + SM_RING + slot * SLOT_BYTES;
                mbar_wait(fb, q12 & 1);
            };
            auto release = [&]() { __syncwarp(); if (lane == 0) mbar_arrive(fb + NS * 8); };
            uint4 qf[4];
            {
                const int p = ph - 1;
                if (!own) mbar_wait(bar_qfull + (p & 1) * 8, (p >> 1) & 1);
                const uint32_t qb = sb + (own ? SM_Q : SM_PQ + (p & 1) * 512) + qoff;
#pragma unroll
                for (int j = 0; j < 4; j++) qf[j] = lds128(qb + ((j ^ (g >> 2)) << 6));
                __syncwarp();
                if (!own && lane == 0) mbar_arrive(bar_qfree + (p & 1) * 8);
            }
            float sv[2][4];
#pragma unroll
            for (int u = 0; u < 2; u++) {
                float sa[4] = {0.f, 0.f, 0.f, 0.f}, sc[4] = {0.f, 0.f, 0.f, 0.f};
                if (u == 0 || two) {
                    acquire(ib + grp + 2 * u);
                    if (u == 0 || use2) {
                        uint4 Lo[4], Hi[4];
                        Lo[0] = lds128(tb + koffA);       Hi[0] = lds128(tb + koffA + 2048);
                        Lo[1] = lds128(tb + koffB);       Hi[1] = lds128(tb + koffB + 2048);
                        Lo[2] = lds128(tb + koffA + 128); Hi[2] = lds128(tb + koffA + 128 + 2048);
                        Lo[3] = lds128(tb + koffB + 128); Hi[3] = lds128(tb + koffB + 128 + 2048);
#pragma unroll
                        for (int j = 0; j < 4; j++) {
                            mma16816(sa, Lo[j].x, Hi[j].x, Lo[j].y, Hi[j].y, qf[j].x, qf[j].y);
                            mma16816(sc, Lo[j].z, Hi[j].z, Lo[j].w, Hi[j].w, qf[j].z, qf[j].w);
                        }
                    }
                    release();
                }
#pragma unroll
                for (int e = 0; e < 4; e++) sv[u][e] = (valid && (u == 0 || use2)) ? sa[e] + sc[e] : -INFINITY;
            }
            float m0 = fmaxf(fmaxf(fmaxf(sv[0][0], sv[0][2]), fmaxf(sv[1][0], sv[1][2])), -3.0e38f);
            float m1 = fmaxf(fmaxf(fmaxf(sv[0][1], sv[0][3]), fmaxf(sv[1][1], sv[1][3])), -3.0e38f);
#pragma unroll
            for (int x = 2; x <= 16; x <<= 1) {
                m0 = fmaxf(m0, __shfl_xor_sync(0xffffffffu, m0, x));
                m1 = fmaxf(m1, __shfl_xor_sync(0xffffffffu, m1, x));
            }
            float l0 = 0.f, l1 = 0.f;
            uint32_t pb[2][4];
#pragma unroll
            for (int u = 0; u < 2; u++) {
                const float p0 = ex2((sv[u][0] - m0) * SCALE_LOG2E), p1 = ex2((sv[u][1] - m1) * SCALE_LOG2E);
                const float p2 = ex2((sv[u][2] - m0) * SCALE_LOG2E), p3 = ex2((sv[u][3] - m1) * SCALE_LOG2E);
                l0 += p0 + p2; l1 += p1 + p3;
                pb[u][0] = pack_bf16(p0, p0) & amask; pb[u][1] = pack_bf16(p1, p1) & amask;
                pb[u][2] = pack_bf16(p2, p2) & amask; pb[u][3] = pack_bf16(p3, p3) & amask;
            }
#pragma unroll
            for (int x = 2; x <= 16; x <<= 1) {
                l0 += __shfl_xor_sync(0xffffffffu, l0, x);
                l1 += __shfl_xor_sync(0xffffffffu, l1, x);
            }
            float acc[16][4];
#pragma unroll
            for (int i = 0; i < 16; i++) { acc[i][0] = acc[i][1] = acc[i][2] = acc[i][3] = 0.f; }
#pragma unroll
            for (int u = 0; u < 2; u++) {
                if (u == 0 || two) {
                    const int i = ib + n + grp + 2 * u;
                    acquire(i);
                    if ((tid & 127) == 0 && u + grp == 1 && ph >= 2 && ph <= CTL_LAST) {
                        const int e = max(min((int)(gtime32() - ctl[i & 15]) - LAT_TARGET, 2000), -1000);
                        asm volatile("red.relaxed.gpu.global.add.u64 [%0], %1;" ::"l"(cword), "l"((unsigned long long)(long long)e << 32) : "memory");
                    }
                    if (u == 0 || use2) {
#pragma unroll
                        for (int j = 0; j < 8; j++) {
                            const uint4 a = ldsm4t(tb + (voff ^ ((j & 3) << 5)) + (j >> 2) * 128);
                            mma16816(acc[j], a.x, a.y, a.z, a.w, pb[u][0], pb[u][2]);
                            mma16816(acc[8 + j], a.x, a.y, a.z, a.w, pb[u][1], pb[u][3]);
                        }
                    }
                    release();
                }
            }
            ib += 2 * n;
            if (ph > 0) mbar_wait(bar_redfree, (ph - 1) & 1);
#pragma unroll
            for (int q = 0; q < 4; q++) {
                float r[8];
#pragma unroll
                for (int y = 0; y < 8; y++) r[y] = acc[4 * q + (y >> 1)][2 * (y & 1)] + acc[4 * q + ((y ^ 4) >> 1)][2 * (y & 1) + 1];
#pragma unroll
                for (int y = 0; y < 8; y += 2) r[y] += __shfl_xor_sync(0xffffffffu, r[y + 1], 1);
                r[0] += __shfl_xor_sync(0xffffffffu, r[2], 2);
                r[4] += __shfl_xor_sync(0xffffffffu, r[6], 2);
                float* dst2 = red + warp * 256 + q * 64 + t * 8 + g;
                dst2[0] = r[0];
                dst2[32] = r[4];
            }
            if (lane == 0) *reinterpret_cast<float4*>(ml + warp * 4) = make_float4(m0, l0, m1, l1);
            __syncwarp();
            if (lane == 0) mbar_arrive(bar_redfull);
            if ((tid & 127) == 0 && ph == CTL_LAST)
                asm volatile("atom.relaxed.gpu.global.add.u64 %0, [%1], %2;" : "=l"(cold) : "l"(cword), "l"(1ull) : "memory");
        }
    } else if (warp == 8) {
        const uint32_t t_entry = gtime32();
        if (lane == 0) {
            asm volatile("prefetch.param.tensormap [%0];" ::"l"(__cvta_generic_to_grid_constant(&P.wq_map[br])) : "memory");
#pragma unroll
            for (int i = 0; i < 8; i++) mbar_init(bar_wq + i * 8, 1);
            asm volatile("fence.mbarrier_init.release.cluster;" ::: "memory");
        }
        __syncwarp();
        uint64_t pol;
        asm volatile("createpolicy.fractional.L2::evict_first.b64 %0, 1.0;" : "=l"(pol));
#pragma unroll
        for (int c = 0; c < 4; c++)
            expect_and_copy_2d(sb + SM_RING + (WQ_SLOT0 + c) * SLOT_BYTES, &P.wq_map[br], h * 256, s * QROWS_PER_CTA + c * 36, bar_wq + c * 8, pol);
        if (lane == 0) {
#pragma unroll
            for (int i = 0; i < 2 * NS; i++) mbar_init(bar_full + i * 8, i >= NS ? 4 : 1);
            mbar_init(bar_pq, 1);
            mbar_init(bar_po, 1);
            mbar_init(bar_qfull, 1); mbar_init(bar_qfull + 8, 1);
            mbar_init(bar_qfree, 8); mbar_init(bar_qfree + 8, 8);
            mbar_init(bar_redfree, 1); mbar_init(bar_redfull, 8); mbar_init(bar_gath, 1);
            asm volatile("fence.mbarrier_init.release.cluster;" ::: "memory");
            mbar_expect_tx(bar_pq, 256 * 4);
            mbar_expect_tx(bar_po, 130 * 4);
#pragma unroll
            for (int i = 0; i < WQ_SLOT0; i++) mbar_arrive_n(bar_empty + i * 8, 4);
            ctl[16] = 0; ctl[17] = 0;
        }
        __syncwarp();
        cluster_arrive();
        bar_arrive(1, 288);
        bar_arrive(3, 128);
#pragma unroll
        for (int c = 4; c < 8; c++)
            expect_and_copy_2d(sb + SM_RING + (WQ_SLOT0 + c) * SLOT_BYTES, &P.wq_map[br], h * 256, s * QROWS_PER_CTA + c * 36, bar_wq + c * 8, pol);
        const unsigned char* kp = reinterpret_cast<const unsigned char*>(P.k[br]);
        const unsigned char* vp = reinterpret_cast<const unsigned char*>(P.v[br]);
        const int own0 = h * 128 + OWN_TILE0 + s * 8;
        const unsigned char* wop = reinterpret_cast<const unsigned char*>(P.wo[br] + (size_t)(h * 256 + s * 128) * D_MODEL);
        if (lane == 0) {
            asm volatile("cp.async.bulk.prefetch.L2.global [%0], 16;" ::"l"(kp + (size_t)own0 * TILE_BYTES));
            asm volatile("cp.async.bulk.prefetch.L2.global [%0], 16;" ::"l"(vp + (size_t)own0 * TILE_BYTES));
            asm volatile("cp.async.bulk.prefetch.L2.global [%0], 16;" ::"l"(wop));
            asm volatile("cp.async.bulk.prefetch.L2.global [%0], 16;" ::"l"(wop + WO_CHUNKS * WO_CHUNK_BYTES - 16));
        }
        __syncwarp();
        if (lane < NPH) {
            const int nt = phase_tiles(lane);
            const int first = lane == 0 ? 0 : 2 * N0 + 8 * (lane - 1) - (lane == NPH - 1 ? 8 - 2 * N1 : 0);
            uint16_t* tab = reinterpret_cast<uint16_t*>(smem + SM_TAB) + first;
#pragma unroll
            for (int u = 0; u < 4; u++) {
                const int e = lane == 0 ? 2 * (own0 + u) : lane == NPH - 2 ? 2 * (own0 + N0 + u) : lane == NPH - 1 ? 2 * (own0 + N0 + N1 + u)
                            : (lane - 1) * 256 + (u < 3 ? 2 * (u * 32 + m) : (192 + m) | 0x4000);
                if (u < nt) { tab[u] = (uint16_t)e; tab[nt + u] = (uint16_t)(e | 0x8000); }
            }
        }
        __syncwarp();
        const uint32_t dt = P.dt, dte = dt + ((dt * 3) >> 7), dtw = dte + (dte >> 3);
        uint32_t tnext = 2 * (t_entry + P.t0) + ((cta * dt) >> 6);
        uint32_t sbar = bar_full, sdst = sb + SM_RING, eph = 0;
        const uint32_t cs = sb + SM_CTL;
        auto issue = [&](int i, const unsigned char* src, uint32_t bytes) {
            mbar_wait(sbar + NS * 8, eph);
            unsigned n = 0;
            uint32_t now, shift;
#pragma unroll 1
            do {
                now = gtime32();
                asm volatile("ld.volatile.shared.u32 %0, [%1];" : "=r"(shift) : "r"(cs + 64) : "memory");
            } while ((int)(2 * (now - shift) - tnext) < 0 && ++n < SPIN_LIMIT);
            expect_and_copy(sdst, src, bytes, sbar, pol);
            asm volatile("st.volatile.shared.u32 [%0], %1;" ::"r"(cs + (i & 15) * 4), "r"(now) : "memory");
            sbar += 8; sdst += SLOT_BYTES;
            if (sbar == bar_empty) { sbar = bar_full; sdst = sb + SM_RING; eph ^= 1; }
        };
        uint32_t ent;
        asm volatile("ld.shared.u16 %0, [%1];" : "=r"(ent) : "r"(sb + SM_TAB) : "memory");
#pragma unroll 1
        for (int i = 0; i < NKV; i++) {
            const unsigned char* src = ((ent & 0x8000) ? vp : kp) + (size_t)((ent & 0x3fff) * (TILE_BYTES / 2));
            const uint32_t hs = (ent >> 14) & 1;
            asm volatile("ld.shared.u16 %0, [%1];" : "=r"(ent) : "r"(sb + SM_TAB + 2 * i + 2) : "memory");
            issue(i, src, TILE_BYTES >> hs);
            tnext += (i >= NKV - 2 * (8 - N0) ? dte : dt) >> hs;
        }
#pragma unroll 1
        for (int i = 0; i < WO_CHUNKS; i++) {
            issue(i, wop + i * WO_CHUNK_BYTES, WO_CHUNK_BYTES);
            tnext += dtw;
        }
        cluster_wait();
    } else if (warp == 11) {
        cluster_arrive();
        bar_sync(3, 128);
        cluster_wait();
        const float* ml = reinterpret_cast<const float*>(smem + SM_ML);
        float Mk[2], Lk[2];
        float4 ok[2];
#pragma unroll 1
        for (int ph = 0; ph < NPH; ph++) {
            mbar_wait(bar_redfull, ph & 1);
            float M[2], L[2];
            float4 o[2];
            float4 w[8];
#pragma unroll
            for (int i = 0; i < 8; i++) w[i] = *reinterpret_cast<const float4*>(ml + i * 4);
            M[0] = w[0].x; M[1] = w[0].z;
#pragma unroll
            for (int i = 1; i < 8; i++) { M[0] = fmaxf(M[0], w[i].x); M[1] = fmaxf(M[1], w[i].z); }
#pragma unroll
            for (int hd = 0; hd < 2; hd++) {
                L[hd] = 0.f; o[hd] = make_float4(0.f, 0.f, 0.f, 0.f);
#pragma unroll
                for (int i = 0; i < 8; i++) {
                    const float f = ex2(((hd ? w[i].z : w[i].x) - M[hd]) * SCALE_LOG2E);
                    const float4 a = *reinterpret_cast<const float4*>(red + i * 256 + hd * 128 + lane * 4);
                    o[hd].x = fmaf(f, a.x, o[hd].x); o[hd].y = fmaf(f, a.y, o[hd].y);
                    o[hd].z = fmaf(f, a.z, o[hd].z); o[hd].w = fmaf(f, a.w, o[hd].w);
                    L[hd] = fmaf(f, hd ? w[i].w : w[i].y, L[hd]);
                }
            }
            __syncwarp();
            if (lane == 0) mbar_arrive(bar_redfree);
#pragma unroll
            for (int hd = 0; hd < 2; hd++) {
                if (ph == 0) {
                    Mk[hd] = M[hd]; Lk[hd] = L[hd]; ok[hd] = o[hd];
                } else if (ph > HKV) {
                    merge4(Mk[hd], Lk[hd], ok[hd], M[hd], L[hd], o[hd]);
                } else {
                    const int rec = (br * NSRC + (ph - 1) * 2 + hd) * NSRC + m;
                    st_rlx4v(P.mail + OB_OFF + rec * 128 + lane * 4, make_uint4(enc(o[hd].x), enc(o[hd].y), enc(o[hd].z), enc(o[hd].w)));
                    if (lane == 0) st_rlx2(P.mail + MB_OFF + rec * 2, enc(M[hd]), enc(L[hd]));
                }
            }
        }
        uint32_t peer;
        asm volatile("mapa.shared::cluster.u32 %0, %1, %2;" : "=r"(peer) : "r"(sb), "r"(s ^ 1));
        const float4 snd = s ? ok[0] : ok[1];
        asm volatile("st.async.shared::cluster.mbarrier::complete_tx::bytes.v4.f32 [%0], {%1,%2,%3,%4}, [%5];"
                     ::"r"(peer + SM_PO + lane * 16), "f"(snd.x), "f"(snd.y), "f"(snd.z), "f"(snd.w), "r"(peer + (bar_po - sb)) : "memory");
        if (lane < 2) st_peer(peer + SM_PO + 512 + lane * 4, lane ? (s ? Lk[0] : Lk[1]) : (s ? Mk[0] : Mk[1]), peer + (bar_po - sb));
        float Mg = s ? Mk[1] : Mk[0], Lg = s ? Lk[1] : Lk[0];
        float4 og = s ? ok[1] : ok[0];
        mbar_wait(bar_gath, 0);
        const float* gbuf = reinterpret_cast<const float*>(smem + SM_G);
        merge4(Mg, Lg, og, gbuf[128], gbuf[129], *reinterpret_cast<const float4*>(gbuf + lane * 4));
        mbar_wait_cluster(bar_po, 0);
        const float* pbuf = reinterpret_cast<const float*>(smem + SM_PO);
        merge4(Mg, Lg, og, pbuf[128], pbuf[129], *reinterpret_cast<const float4*>(pbuf + lane * 4));
        const float inv = __fdividef(1.0f, Lg);
        *reinterpret_cast<uint2*>(smem + SM_O + lane * 8) = make_uint2(pack_bf16(og.x * inv, og.y * inv), pack_bf16(og.z * inv, og.w * inv));
        bar_arrive(2, 320);
        return;
    } else {
        cluster_arrive();
        bar_sync(3, 128);
        cluster_wait();
        if (warp == 10) {
            uint32_t* qin = P.mail + QB_OFF + cta * HKV * 128 + lane * 4;
            uint4 cur = ld_rlx4(qin), nxt = ld_rlx4(qin + 128);
#pragma unroll 1
            for (int p = 0; p < HKV; p++) {
                if (lane == 0 && p + 1 < HKV) {
                    const size_t off = ((size_t)(p + 1) * SK + m * TILE_KEYS) * DH;
                    asm volatile("cp.async.bulk.prefetch.L2.global [%0], 16;" ::"l"(P.k[br] + off));
                    asm volatile("cp.async.bulk.prefetch.L2.global [%0], 16;" ::"l"(P.v[br] + off));
                }
                __syncwarp();
                mbar_wait(bar_qfree + (p & 1) * 8, (p >> 1) & 1);
                unsigned n = 0;
#pragma unroll 1
                while (min4(cur) == 0 && ++n < SPIN_LIMIT) cur = ld_rlx4(qin + p * 128);
                *reinterpret_cast<uint4*>(smem + SM_PQ + (p & 1) * 512 + lane * 16) = cur;
                __syncwarp();
                if (lane == 0) mbar_arrive(bar_qfull + (p & 1) * 8);
                st_rlx4(qin + p * 128, 0u);
                cur = nxt;
                nxt = make_uint4(0u, 0u, 0u, 0u);
            }
        }
        {
            uint32_t* mbox = P.mail + MB_OFF + (cta * NSRC + lane) * 2;
            bool pending = warp == 9;
            unsigned n = 0;
#pragma unroll 1
            while (++n < SPIN_LIMIT) {
                const bool run = __shfl_sync(0xffffffffu, ctl[17], 0) == 0;
                if (!run && !pending) break;
                if (run) __nanosleep(CTL_NAP);
                if (warp != 9) continue;
                uint2 y = make_uint2(0u, 0u);
                if (pending) y = ld_rlx2(mbox);
                if (run) {
                    const int sum = (int)ld_rlx(reinterpret_cast<const uint32_t*>(cword) + 1);
                    if (lane == 0) ctl[16] = (uint32_t)max(min(((sum >> 6) * CTL_GAIN) >> 8, 20000), -20000);
                }
                if (__all_sync(0xffffffffu, min(y.x, y.y) != 0)) {
                    pending = false;
                    uint32_t* box = P.mail + OB_OFF + cta * NSRC * 128 + lane * 4;
                    uint4 v[NSRC];
                    uint32_t z;
                    unsigned n2 = 0;
#pragma unroll 1
                    do {
#pragma unroll
                        for (int i = 0; i < NSRC; i++) v[i] = ld_rlx4(box + i * 128);
                        z = 0xffffffffu;
#pragma unroll
                        for (int i = 0; i < NSRC; i++) z = min(z, min4(v[i]));
                    } while (z == 0 && ++n2 < SPIN_LIMIT);
                    __syncwarp();
                    float Mg = dec(y.x);
#pragma unroll
                    for (int x = 1; x <= 16; x <<= 1) Mg = fmaxf(Mg, __shfl_xor_sync(0xffffffffu, Mg, x));
                    const float f = ex2((dec(y.x) - Mg) * SCALE_LOG2E);
                    float Lg = f * dec(y.y);
#pragma unroll
                    for (int x = 1; x <= 16; x <<= 1) Lg += __shfl_xor_sync(0xffffffffu, Lg, x);
                    float4 og = make_float4(0.f, 0.f, 0.f, 0.f);
#pragma unroll
                    for (int i = 0; i < NSRC; i++) {
                        const float fi = __shfl_sync(0xffffffffu, f, i);
                        og.x = fmaf(fi, dec(v[i].x), og.x); og.y = fmaf(fi, dec(v[i].y), og.y);
                        og.z = fmaf(fi, dec(v[i].z), og.z); og.w = fmaf(fi, dec(v[i].w), og.w);
                    }
                    float* gbuf = reinterpret_cast<float*>(smem + SM_G);
                    *reinterpret_cast<float4*>(gbuf + lane * 4) = og;
                    if (lane == 0) { gbuf[128] = Mg; gbuf[129] = Lg; }
                    __syncwarp();
                    if (lane == 0) mbar_arrive(bar_gath);
#pragma unroll 4
                    for (int i = 0; i < NSRC; i++) st_rlx4(box + i * 128, 0u);
                    st_rlx2(mbox, 0u, 0u);
                }
            }
        }
        __syncwarp();
        const int ridx = 2 * m + (warp - 9);
        if (ridx < NRED) {
            uint32_t* rin = rbox + ((br * NRED + ridx) * NSRC + (lane >> 2)) * 16 + (lane & 3) * 4;
            uint32_t* outp = reinterpret_cast<uint32_t*>(P.out + br * D_MODEL + ridx * 16) + (lane & 7);
            const bool hi = lane & 4;
            uint4 r[4];
            unsigned n = 0;
            float a0, a1, a2, a3;
            auto take = [&](const uint4 (&v)[4]) {
                a0 = (dec(v[0].x) + dec(v[1].x)) + (dec(v[2].x) + dec(v[3].x));
                a1 = (dec(v[0].y) + dec(v[1].y)) + (dec(v[2].y) + dec(v[3].y));
                a2 = (dec(v[0].z) + dec(v[1].z)) + (dec(v[2].z) + dec(v[3].z));
                a3 = (dec(v[0].w) + dec(v[1].w)) + (dec(v[2].w) + dec(v[3].w));
                return __all_sync(0xffffffffu, min(min(min4(v[0]), min4(v[1])), min(min4(v[2]), min4(v[3]))) != 0);
            };
#pragma unroll 1
            do {
#pragma unroll
                for (int i = 0; i < 4; i++) r[i] = ld_rlx4(rin + i * 128);
            } while (!take(r) && ++n < SPIN_LIMIT);
            float lo = (hi ? a1 : a0) + __shfl_xor_sync(0xffffffffu, hi ? a0 : a1, 4);
            float up = (hi ? a3 : a2) + __shfl_xor_sync(0xffffffffu, hi ? a2 : a3, 4);
            lo += __shfl_xor_sync(0xffffffffu, lo, 8);  up += __shfl_xor_sync(0xffffffffu, up, 8);
            lo += __shfl_xor_sync(0xffffffffu, lo, 16); up += __shfl_xor_sync(0xffffffffu, up, 16);
            if (lane < 8) asm volatile("st.global.u32 [%0], %1;" ::"l"(outp), "r"(pack_bf16(lo, up)) : "memory");
#pragma unroll
            for (int i = 0; i < 4; i++) st_rlx4(rin + i * 128, 0u);
        }
        return;
    }

    {
        const int i8 = lane & 7;
        const uint32_t woff = sb + SM_RING + (8 * (lane >> 4) + i8) * WO_ROW_BYTES + warp * 128 + ((((lane >> 3) & 1) ^ i8) << 4);
        const uint32_t omask = (t == (g >> 1)) ? ((g & 1) ? 0xffff0000u : 0x0000ffffu) : 0u;
        uint32_t* rout = rbox + ((br * NRED + 4 * warp + t) * NSRC + m) * 16 + 2 * g;
        float c[4][4], c2[4][4];
#pragma unroll
        for (int i = 0; i < 4; i++) { c[i][0] = c[i][1] = c[i][2] = c[i][3] = 0.f; c2[i][0] = c2[i][1] = c2[i][2] = c2[i][3] = 0.f; }
        bar_sync(2, 320);
        const uint32_t* o32 = reinterpret_cast<const uint32_t*>(smem + SM_O);
        uint32_t ob[2 * WO_CHUNKS];
#pragma unroll
        for (int j = 0; j < 2 * WO_CHUNKS; j++) ob[j] = o32[4 * j + t] & omask;
#pragma unroll
        for (int ks = 0; ks < WO_CHUNKS - 2; ks += 2) {
            mbar_wait(bar_full + ((NKV + ks) % NS) * 8, ((NKV + ks) / NS) & 1);
            mbar_wait(bar_full + ((NKV + ks + 1) % NS) * 8, ((NKV + ks + 1) / NS) & 1);
            uint4 a[8];
#pragma unroll
            for (int j = 0; j < 8; j++) a[j] = ldsm4t((woff ^ ((j & 3) << 5)) + ((NKV + ks + (j >> 2)) % NS) * SLOT_BYTES);
#pragma unroll
            for (int j = 0; j < 4; j++) {
                mma16816(c[j], a[j].x, a[j].y, a[j].z, a[j].w, ob[2 * ks], ob[2 * ks + 1]);
                mma16816(c2[j], a[4 + j].x, a[4 + j].y, a[4 + j].z, a[4 + j].w, ob[2 * ks + 2], ob[2 * ks + 3]);
            }
        }
#pragma unroll
        for (int ks = WO_CHUNKS - 2; ks < WO_CHUNKS; ks++) {
            mbar_wait(bar_full + ((NKV + ks) % NS) * 8, ((NKV + ks) / NS) & 1);
#pragma unroll
            for (int j = 0; j < 4; j++) {
                const uint4 a = ldsm4t((woff ^ (j << 5)) + ((NKV + ks) % NS) * SLOT_BYTES);
                if (ks & 1) mma16816(c[j], a.x, a.y, a.z, a.w, ob[2 * ks], ob[2 * ks + 1]);
                else mma16816(c2[j], a.x, a.y, a.z, a.w, ob[2 * ks], ob[2 * ks + 1]);
            }
        }
        float r[8];
#pragma unroll
        for (int y = 0; y < 8; y++)
            r[y] = (c2[y >> 1][2 * (y & 1)] + c2[y >> 1][2 * ((y ^ 1) & 1) + 1]) + (c[y >> 1][2 * (y & 1)] + c[y >> 1][2 * ((y ^ 1) & 1) + 1]);
        r[0] += __shfl_xor_sync(0xffffffffu, r[2], 1);
        r[1] += __shfl_xor_sync(0xffffffffu, r[3], 1);
        r[4] += __shfl_xor_sync(0xffffffffu, r[6], 1);
        r[5] += __shfl_xor_sync(0xffffffffu, r[7], 1);
        r[0] += __shfl_xor_sync(0xffffffffu, r[4], 2);
        r[1] += __shfl_xor_sync(0xffffffffu, r[5], 2);
        st_rlx2(rout, enc(r[0]), enc(r[1]));
        if ((uint32_t)cold == 2 * NCTA - 1)
            asm volatile("st.relaxed.gpu.global.u64 [%0], %1;" ::"l"(cword), "l"(0ull) : "memory");
    }
}

}

extern "C" void kernel_launch(void* const* d_in, const int* in_sizes, int n_in, void* d_out, int out_size) {
    (void)in_sizes; (void)n_in; (void)out_size;
    typedef CUresult (*EncodeFn)(CUtensorMap*, CUtensorMapDataType, cuuint32_t, void*, const cuuint64_t*, const cuuint64_t*,
                                 const cuuint32_t*, const cuuint32_t*, CUtensorMapInterleave, CUtensorMapSwizzle,
                                 CUtensorMapL2promotion, CUtensorMapFloatOOBfill);
    static EncodeFn encode = nullptr;
    static uint32_t* mail = nullptr;
    static int dt = 650;
    if (!mail) {
        cudaFuncSetAttribute(gqa_decode_fused, cudaFuncAttributeMaxDynamicSharedMemorySize, SM_TOTAL);
        void* p = nullptr;
        cudaGetSymbolAddress(&p, g_mail);
        mail = (uint32_t*)p;
        cudaDriverEntryPointQueryResult qres = cudaDriverEntryPointSymbolNotFound;
        cudaGetDriverEntryPoint("cuTensorMapEncodeTiled", &p, cudaEnableDefault, &qres);
        encode = (qres == cudaDriverEntryPointSuccess) ? (EncodeFn)p : nullptr;
        int dev = 0, khz = 0, bits = 0;
        cudaGetDevice(&dev);
        if (cudaDeviceGetAttribute(&khz, cudaDevAttrMemoryClockRate, dev) == cudaSuccess &&
            cudaDeviceGetAttribute(&bits, cudaDevAttrGlobalMemoryBusWidth, dev) == cudaSuccess && khz > 0 && bits > 0) {
            const double bytes_per_ns = 2.0 * khz * 1e-6 * bits / 8.0;
            dt = (int)(2.0 * NCTA * TILE_BYTES / (0.9625 * bytes_per_ns) + 0.5);
        }
        (void)cudaGetLastError();
    }
    if (!encode) return;
    Params p;
    for (int b = 0; b < 2; b++) {
        p.x[b] = (const __nv_bfloat16*)d_in[5 * b + 0];
        p.k[b] = (const __nv_bfloat16*)d_in[5 * b + 1];
        p.v[b] = (const __nv_bfloat16*)d_in[5 * b + 2];
        p.wq[b] = (const __nv_bfloat16*)d_in[5 * b + 3];
        p.wo[b] = (const __nv_bfloat16*)d_in[5 * b + 4];
        const cuuint64_t dims[2] = {(cuuint64_t)QCOLS, (cuuint64_t)D_MODEL};
        const cuuint64_t strides[1] = {(cuuint64_t)QCOLS * 2};
        const cuuint32_t box[2] = {256, 36}, estr[2] = {1, 1};
        encode(&p.wq_map[b], CU_TENSOR_MAP_DATA_TYPE_BFLOAT16, 2, d_in[5 * b + 3], dims, strides, box, estr,
               CU_TENSOR_MAP_INTERLEAVE_NONE, CU_TENSOR_MAP_SWIZZLE_NONE, CU_TENSOR_MAP_L2_PROMOTION_NONE,
               CU_TENSOR_MAP_FLOAT_OOB_FILL_NONE);
    }
    p.out = (__nv_bfloat16*)d_out;
    p.mail = mail;
    p.dt = dt;
    p.t0 = dt * 9 / 2 > T0_LEAD ? dt * 9 / 2 - T0_LEAD : 0;
    gqa_decode_fused<<<NCTA, NTHREADS, SM_TOTAL>>>(p);
}
```
